```python
import torch

def _softmax(x, axis=-1):
    return torch.softmax(x, dim=axis)

def _gelu(x):
    return torch.nn.functional.gelu(x, approximate='tanh')

def _silu(x):
    return torch.nn.functional.silu(x)

def _sigmoid(x):
    return torch.sigmoid(x)

def _layernorm(x, axis=-1, eps=1e-05):
    m = x.mean(dim=axis, keepdim=True)
    v = x.var(dim=axis, keepdim=True, unbiased=False)
    return (x - m) / torch.sqrt(v + eps)

def _scatter_add(tgt, idx, src, axis=0):
    return tgt.clone().index_add_(axis, idx, src)

def _segment_sum(src, seg, n):
    out = torch.zeros((n,) + src.shape[1:], dtype=src.dtype)
    return out.index_add_(0, seg, src)

def _pad(x, pw):
    flat = tuple((v for pair in reversed(pw) for v in pair))
    return torch.nn.functional.pad(x, flat)
kernel_name = 'gated_mix__memory_aug_recurrent_mem_tr__glu_gated_glu__prompt'

def setup_inputs():

    _w = lambda a: (lambda t: t.to(torch.bfloat16) if t.is_floating_point() else t)(torch.as_tensor(a))

    def _A_setup():
        B, S, Dm = (1, 2048, 512)
        H, Dh = (32, 128)
        M, seg = (8, 32)
        seg = min(seg, S)
        S = S // seg * seg
        return {'x': _w((lambda *s: torch.randn(*s, dtype=torch.bfloat16) * 0.05)(B, S, Dm)), 'mem0': _w((lambda *s: torch.randn(*s, dtype=torch.bfloat16) * 0.8)(B, M, Dm)), 'Wq': _w((lambda *s: torch.randn(*s, dtype=torch.bfloat16) * 1.6)(Dm, H, Dh) * Dm ** (-0.5)), 'Wk': _w((lambda *s: torch.randn(*s, dtype=torch.bfloat16) * 1.6)(Dm, H, Dh) * Dm ** (-0.5)), 'Wv': _w((lambda *s: torch.randn(*s, dtype=torch.bfloat16) * 0.8)(Dm, H, Dh) * Dm ** (-0.5)), 'Wo': _w((lambda *s: torch.randn(*s, dtype=torch.bfloat16) * 0.8)(H, Dh, Dm) * (H * Dh) ** (-0.5)), 'seg_len': seg}
    _A_in = _A_setup()

    def _B_setup():
        B, S, D, F = (1, 2048, 512, 1792)
        return {'x': _w((lambda *s: torch.randn(*s, dtype=torch.bfloat16) * 0.05)(B, S, D)), 'w_gate': _w((lambda *s: torch.randn(*s, dtype=torch.bfloat16) * 0.4)(D, F)), 'w_up': _w((lambda *s: torch.randn(*s, dtype=torch.bfloat16) * 0.05)(D, F)), 'w_down': _w((lambda *s: torch.randn(*s, dtype=torch.bfloat16) * 0.05)(F, D))}
    _B_in = _B_setup()
    return {'A_x': _A_in['x'], 'A_mem0': _A_in['mem0'], 'A_Wq': _A_in['Wq'], 'A_Wk': _A_in['Wk'], 'A_Wv': _A_in['Wv'], 'A_Wo': _A_in['Wo'], 'A_seg_len': _A_in['seg_len'], 'B_x': _B_in['x'], 'B_w_gate': _B_in['w_gate'], 'B_w_up': _B_in['w_up'], 'B_w_down': _B_in['w_down'], 'gate_w': _w((lambda *s: torch.randn(*s, dtype=torch.bfloat16) * 0.05)(512) * 16.0)}

def reference(A_x, A_mem0, A_Wq, A_Wk, A_Wv, A_Wo, A_seg_len, B_x, B_w_gate, B_w_up, B_w_down, gate_w):

    def _A_ref(x, mem0, Wq, Wk, Wv, Wo, seg_len):
        B, S, Dm = x.shape
        H, Dh = (Wq.shape[1], Wq.shape[2])
        M = mem0.shape[1]
        scale = Dh ** (-0.5)
        n_seg = S // seg_len
        L = M + seg_len
        idx = torch.arange(L)
        mask = (idx[:, None] < M) | (idx[:, None] >= idx[None, :])
        mem = mem0
        outs = []
        for s in range(n_seg):
            xs = x[:, s * seg_len:(s + 1) * seg_len, :].clone()
            h = torch.concatenate([mem, xs], axis=1)
            q = torch.einsum('btd,dhe->bhte', h, Wq)
            k = torch.einsum('btd,dhe->bhte', h, Wk)
            v = torch.einsum('btd,dhe->bhte', h, Wv)
            scores = torch.einsum('bhqe,bhke->bhqk', q, k) * scale
            scores = torch.where(mask[None, None], scores, -1000000000.0)
            p = _softmax(scores, axis=-1)
            o = torch.einsum('bhqk,bhke->bhqe', p, v)
            o = torch.einsum('bhte,hed->btd', o, Wo)
            mem = o[:, :M, :].clone()
            outs.append(o[:, M:, :])
        return torch.concatenate(outs, axis=1)

    def _B_ref(x, w_gate, w_up, w_down):
        g = torch.einsum('bsd,df->bsf', x, w_gate)
        u = torch.einsum('bsd,df->bsf', x, w_up)
        h = _sigmoid(g) * u
        return torch.einsum('bsf,fd->bsd', h, w_down)
    x = A_x
    g = _sigmoid((x * gate_w).sum(-1, keepdims=True))
    a = _A_ref(x, A_mem0, A_Wq, A_Wk, A_Wv, A_Wo, A_seg_len)
    b = _B_ref(x, B_w_gate, B_w_up, B_w_down)
    return g * a + (1 - g) * b
```

```cpp
#include <cuda_runtime.h>
#include <cuda_bf16.h>
#include <cuda_fp16.h>
#include <cuda.h>
#include <stdint.h>

typedef __nv_bfloat16 bf16;

constexpr int SEQ = 2048, DM = 512, NH = 32, DH = 128, NM = 8, SEGL = 32, NSEG = 64, FF = 1792;
constexpr int HD = NH * DH;
constexpr int BLK_BYTES = 24576;
constexpr int RING_SLOT = 80 * 256;
constexpr int SPIN_LIMIT = 1 << 22;

__device__ __align__(1024) uint8_t g_qkv[(size_t)NSEG * NH * BLK_BYTES];
__device__ __align__(1024) bf16 g_o[(size_t)SEQ * HD];
__device__ __align__(1024) bf16 g_h[(size_t)SEQ * FF];
__device__ __align__(1024) uint8_t g_ring[4 * RING_SLOT];
__device__ float g_gate[SEQ];
__device__ uint4 g_pub[64];
__device__ unsigned g_done;
__device__ int g_err;

__device__ __forceinline__ uint32_t smem_u32(const void* p) { return (uint32_t)__cvta_generic_to_shared(p); }
__device__ __forceinline__ uint32_t mapa(uint32_t a, uint32_t rank) { uint32_t r; asm volatile("mapa.shared::cluster.u32 %0, %1, %2;" : "=r"(r) : "r"(a), "r"(rank)); return r; }
__device__ __forceinline__ void mbar_init(uint32_t a, uint32_t cnt) { asm volatile("mbarrier.init.shared::cta.b64 [%0], %1;" :: "r"(a), "r"(cnt) : "memory"); }
__device__ __forceinline__ void mbar_expect_tx(uint32_t a, uint32_t bytes) { asm volatile("mbarrier.arrive.expect_tx.shared::cta.b64 _, [%0], %1;" :: "r"(a), "r"(bytes) : "memory"); }
__device__ __forceinline__ bool mbar_try(uint32_t a, uint32_t parity) {
  uint32_t ok;
  asm volatile("{ .reg .pred p; mbarrier.try_wait.parity.shared::cta.b64 p, [%1], %2; selp.u32 %0, 1, 0, p; }" : "=r"(ok) : "r"(a), "r"(parity) : "memory");
  return ok;
}
__device__ __forceinline__ bool mbar_try_cluster(uint32_t a, uint32_t parity) {
  uint32_t ok;
  asm volatile("{ .reg .pred p; mbarrier.try_wait.parity.acquire.cluster.shared::cta.b64 p, [%1], %2; selp.u32 %0, 1, 0, p; }" : "=r"(ok) : "r"(a), "r"(parity) : "memory");
  return ok;
}
__device__ __forceinline__ void mbar_wait(uint32_t a, uint32_t parity) {
  int it = 0;
  while (!mbar_try(a, parity)) { if (++it > SPIN_LIMIT) { g_err = 1; break; } }
}
__device__ __forceinline__ void mbar_wait_cluster(uint32_t a, uint32_t parity) {
  int it = 0;
  while (!mbar_try_cluster(a, parity)) { if (++it > SPIN_LIMIT) { g_err = 2; break; } }
}
template <int ID, int N> __device__ __forceinline__ void bar_sync() { asm volatile("bar.sync %0, %1;" :: "n"(ID), "n"(N) : "memory"); }
template <int ID, int N> __device__ __forceinline__ void bar_arrive() { asm volatile("bar.arrive %0, %1;" :: "n"(ID), "n"(N) : "memory"); }
__device__ __forceinline__ void bar_sync_id(int id, int n) { asm volatile("bar.sync %0, %1;" :: "r"(id), "r"(n) : "memory"); }
__device__ __forceinline__ void tma2d(uint32_t dst, const CUtensorMap* tm, int c0, int c1, uint32_t mb) {
  asm volatile("cp.async.bulk.tensor.2d.shared::cluster.global.mbarrier::complete_tx::bytes [%0], [%1, {%3, %4}], [%2];"
               :: "r"(dst), "l"((uint64_t)tm), "r"(mb), "r"(c0), "r"(c1) : "memory");
}
__device__ __forceinline__ void bulk_g2s(uint32_t dst, const void* src, uint32_t bytes, uint32_t mb) {
  asm volatile("cp.async.bulk.shared::cluster.global.mbarrier::complete_tx::bytes [%0], [%1], %2, [%3];"
               :: "r"(dst), "l"(src), "r"(bytes), "r"(mb) : "memory");
}
__device__ __forceinline__ void ldm4(uint32_t* r, uint32_t a) {
  asm volatile("ldmatrix.sync.aligned.m8n8.x4.shared.b16 {%0,%1,%2,%3}, [%4];" : "=r"(r[0]), "=r"(r[1]), "=r"(r[2]), "=r"(r[3]) : "r"(a) : "memory");
}
__device__ __forceinline__ void ldm4t(uint32_t* r, uint32_t a) {
  asm volatile("ldmatrix.sync.aligned.m8n8.x4.trans.shared.b16 {%0,%1,%2,%3}, [%4];" : "=r"(r[0]), "=r"(r[1]), "=r"(r[2]), "=r"(r[3]) : "r"(a) : "memory");
}
__device__ __forceinline__ void stm4(uint32_t a, uint32_t r0, uint32_t r1, uint32_t r2, uint32_t r3) {
  asm volatile("stmatrix.sync.aligned.m8n8.x4.shared.b16 [%0], {%1,%2,%3,%4};" :: "r"(a), "r"(r0), "r"(r1), "r"(r2), "r"(r3) : "memory");
}
__device__ __forceinline__ void mma16(float* d, uint32_t a0, uint32_t a1, uint32_t a2, uint32_t a3, uint32_t b0, uint32_t b1) {
  asm volatile("mma.sync.aligned.m16n8k16.row.col.f32.bf16.bf16.f32 {%0,%1,%2,%3}, {%4,%5,%6,%7}, {%8,%9}, {%0,%1,%2,%3};"
               : "+f"(d[0]), "+f"(d[1]), "+f"(d[2]), "+f"(d[3]) : "r"(a0), "r"(a1), "r"(a2), "r"(a3), "r"(b0), "r"(b1));
}
__device__ __forceinline__ void mma16z(float* d, uint32_t a0, uint32_t a1, uint32_t a2, uint32_t a3, uint32_t b0, uint32_t b1) {
  asm volatile("mma.sync.aligned.m16n8k16.row.col.f32.bf16.bf16.f32 {%0,%1,%2,%3}, {%4,%5,%6,%7}, {%8,%9}, {%10,%10,%10,%10};"
               : "=f"(d[0]), "=f"(d[1]), "=f"(d[2]), "=f"(d[3]) : "r"(a0), "r"(a1), "r"(a2), "r"(a3), "r"(b0), "r"(b1), "f"(0.f));
}
__device__ __forceinline__ void mma8(float* d, uint32_t a0, uint32_t a1, uint32_t b0) {
  asm volatile("mma.sync.aligned.m16n8k8.row.col.f32.bf16.bf16.f32 {%0,%1,%2,%3}, {%4,%5}, {%6}, {%0,%1,%2,%3};"
               : "+f"(d[0]), "+f"(d[1]), "+f"(d[2]), "+f"(d[3]) : "r"(a0), "r"(a1), "r"(b0));
}
__device__ __forceinline__ void mma8z(float* d, uint32_t a0, uint32_t a1, uint32_t b0) {
  asm volatile("mma.sync.aligned.m16n8k8.row.col.f32.bf16.bf16.f32 {%0,%1,%2,%3}, {%4,%5}, {%6}, {%7,%7,%7,%7};"
               : "=f"(d[0]), "=f"(d[1]), "=f"(d[2]), "=f"(d[3]) : "r"(a0), "r"(a1), "r"(b0), "f"(0.f));
}
__device__ __forceinline__ uint32_t pack_bf16(float lo, float hi) { uint32_t r; asm("cvt.rn.bf16x2.f32 %0, %1, %2;" : "=r"(r) : "f"(hi), "f"(lo)); return r; }
__device__ __forceinline__ uint32_t pack_f16(float lo, float hi) { uint32_t r; asm("cvt.rn.f16x2.f32 %0, %1, %2;" : "=r"(r) : "f"(hi), "f"(lo)); return r; }
__device__ __forceinline__ float2 unpack_f16(uint32_t v) { return __half22float2(*reinterpret_cast<__half2*>(&v)); }
__device__ __forceinline__ uint32_t absmax2(uint32_t a, uint32_t b) { uint32_t r; asm("max.xorsign.abs.bf16x2 %0, %1, %2;" : "=r"(r) : "r"(a), "r"(b)); return r; }
__device__ __forceinline__ uint32_t fold_absmax(uint32_t m) { m &= 0x7FFF7FFFu; return max(m & 0xFFFFu, m >> 16); }
__device__ __forceinline__ float ex2(float x) { float r; asm("ex2.approx.ftz.f32 %0, %1;" : "=f"(r) : "f"(x)); return r; }
__device__ __forceinline__ void sts32(uint32_t a, uint32_t v) { asm volatile("st.shared.u32 [%0], %1;" :: "r"(a), "r"(v) : "memory"); }
__device__ __forceinline__ void sts64f(uint32_t a, float x, float y) { asm volatile("st.shared.v2.f32 [%0], {%1,%2};" :: "r"(a), "f"(x), "f"(y) : "memory"); }
__device__ __forceinline__ float2 lds64f(uint32_t a) { float2 v; asm volatile("ld.shared.v2.f32 {%0,%1}, [%2];" : "=f"(v.x), "=f"(v.y) : "r"(a) : "memory"); return v; }
__device__ __forceinline__ uint32_t lds32(uint32_t a) { uint32_t v; asm volatile("ld.shared.u32 %0, [%1];" : "=r"(v) : "r"(a) : "memory"); return v; }
__device__ __forceinline__ uint4 lds128(uint32_t a) { uint4 v; asm volatile("ld.shared.v4.u32 {%0,%1,%2,%3}, [%4];" : "=r"(v.x), "=r"(v.y), "=r"(v.z), "=r"(v.w) : "r"(a) : "memory"); return v; }
__device__ __forceinline__ void st_async32(uint32_t a, uint32_t v, uint32_t mb) {
  asm volatile("st.async.weak.shared::cluster.mbarrier::complete_tx::bytes.b32 [%0], %1, [%2];" :: "r"(a), "r"(v), "r"(mb) : "memory");
}
__device__ __forceinline__ uint4 ldv128(const void* p) {
  uint4 v; asm volatile("ld.volatile.global.v4.u32 {%0,%1,%2,%3}, [%4];" : "=r"(v.x), "=r"(v.y), "=r"(v.z), "=r"(v.w) : "l"(p) : "memory"); return v;
}
__device__ __forceinline__ uint32_t ldv32(const void* p) { uint32_t v; asm volatile("ld.volatile.global.u32 %0, [%1];" : "=r"(v) : "l"(p) : "memory"); return v; }
__device__ __forceinline__ float bf_lo(uint32_t v) { return __uint_as_float(v << 16); }
__device__ __forceinline__ float bf_hi(uint32_t v) { return __uint_as_float(v & 0xFFFF0000u); }

constexpr int C_WV = 0, C_WO = 65536, C_KVQ = 131072, KVQ_ST = 20480, C_MEM = 192512, C_QM = 200704, QM_BUF = 6144,
              C_OT = 212992, C_SX = 215040, C_VP = 216064, C_MISC = 218112;
constexpr int MB_WQ = C_MISC, MB_WK = C_MISC + 8, MB_WV = C_MISC + 16, MB_WO = C_MISC + 24, MB_PEER = C_MISC + 32  , MB_KVQ = C_MISC + 48  ;
constexpr int C_MX = C_MISC + 128;
constexpr int C_SC = C_MISC + 160;
constexpr int C_WM = C_MISC + 192;
constexpr int C_XE = C_MISC + 256;
constexpr int C_SMEM = C_MISC + 1024;

#define STAMP(slot)

struct ChainArgs { const bf16* x; const bf16* mem0; const bf16* wo; const bf16* gate_w; };

__global__ void __launch_bounds__(384, 1)
chain_kernel(const __grid_constant__ CUtensorMap tmq, const __grid_constant__ CUtensorMap tmk, const __grid_constant__ CUtensorMap tmv,
             const __grid_constant__ CUtensorMap tmo, const ChainArgs args) {
  extern __shared__ __align__(1024) uint8_t smem[];
  const int tid = threadIdx.x, lane = tid & 31, warp = tid >> 5;
  const int cta = blockIdx.x, h = cta >> 1, j = cta & 1;
  uint32_t sb = smem_u32(smem);
  const int g = lane >> 2, t = lane & 3;

  if (tid == 0) {
    mbar_init(sb + MB_WQ, 1); mbar_init(sb + MB_WK, 1); mbar_init(sb + MB_WV, 1); mbar_init(sb + MB_WO, 1);
    mbar_init(sb + MB_PEER, 1); mbar_init(sb + MB_PEER + 8, 1);
    for (int i = 0; i < 3; i++) mbar_init(sb + MB_KVQ + 8 * i, 1);
    asm volatile("fence.mbarrier_init.release.cluster;" ::: "memory");
    const int col = h * DH + j * 64;
    mbar_expect_tx(sb + MB_WQ, 65536); tma2d(sb + C_WO, &tmq, col, 0, sb + MB_WQ); tma2d(sb + C_WO + 32768, &tmq, col, 256, sb + MB_WQ);
    mbar_expect_tx(sb + MB_WK, 65536); tma2d(sb + C_KVQ, &tmk, col, 0, sb + MB_WK); tma2d(sb + C_KVQ + 32768, &tmk, col, 256, sb + MB_WK);
    mbar_expect_tx(sb + MB_WV, 65536); tma2d(sb + C_WV, &tmv, col, 0, sb + MB_WV); tma2d(sb + C_WV + 32768, &tmv, col, 256, sb + MB_WV);
    mbar_expect_tx(sb + MB_PEER, 3072); mbar_expect_tx(sb + MB_PEER + 8, 3072);
  }
  const uint32_t tag = (ldv32(&g_done) >> 6) + 1;
  asm volatile("barrier.cluster.arrive.aligned; barrier.cluster.wait.aligned;" ::: "memory");

  if (warp < 8) {
    asm volatile("setmaxnreg.inc.sync.aligned.u32 224;");
    const int gam = warp >> 2, w = warp & 3;
    uint32_t wa[32][4], R[16][4];
    const uint32_t wlane = ((lane & 7) + ((lane >> 4) << 3)) * 128 + (((2 * w + ((lane >> 3) & 1)) ^ (lane & 7)) << 4);
    {
      mbar_wait(sb + (gam ? MB_WK : MB_WQ), 0);
      const uint32_t src = sb + (gam ? C_KVQ : C_WO) + wlane;
#pragma unroll
      for (int i = 0; i < 32; i++) ldm4t(wa[i], src + (((i + 16 * gam) & 31) << 11));
    }
    bar_sync<10, 384>();
    const uint32_t wv_a = sb + C_WV + gam * 32768 + wlane;
    const uint32_t wo_a = sb + C_WO + (warp >> 1) * 16384 + ((lane & 7) + ((lane >> 4) << 3)) * 128 +
                          ((((warp & 1) * 4 + ((lane >> 3) & 1)) ^ (lane & 7)) << 4);
    mbar_wait(sb + MB_WV, 0);
    {
      uint32_t m = 0;
#pragma unroll
      for (int i = 0; i < 16; i++) {
        ldm4t(R[i], wv_a + (i << 11));
        m = absmax2(absmax2(m, absmax2(R[i][0], R[i][1])), absmax2(R[i][2], R[i][3]));
      }
      m = __reduce_max_sync(~0u, fold_absmax(m));
      if (lane == 0) sts32(sb + C_WM + warp * 4, m);
      bar_arrive<11, 384>();
    }
    const uint32_t mem_st = sb + C_MEM + (warp * 32 + lane) * 16;
    const uint32_t mem_ld0 = sb + C_MEM + gam * 4096 + lane * 16;
    const uint32_t mem_ld1 = sb + C_MEM + (gam ^ 1) * 4096 + lane * 16;
    const uint32_t qrow = 32 * (2 * j + (w >> 1)) + 8 * (g >> 1) + ((4 * (w & 1)) ^ (g & 6)) + (g & 1);
    const uint32_t qm_st = sb + C_QM + qrow * 16 + t * 4;
    const uint32_t peer_d = mapa(sb, j ^ 1) - sb;
    const uint32_t vp_st = sb + C_VP + (w * 64 + gam * 32 + lane) * 8;
    const uint32_t ot_ld = sb + C_OT + (lane ^ (((lane >> 3) & 3) << 1)) * 16;
    uint8_t* const ring_l = g_ring + (warp * 5 + (lane >> 3)) * 256 + (lane & 7) * 16;
    const int ring_s = (4 - (lane >> 3)) * 256 + lane * 4 - (lane & 7) * 16;

    for (int s = 0; s < NSEG; s++) {
      uint32_t pk[8];
      if (s == 0) {
        const unsigned short* m0 = reinterpret_cast<const unsigned short*>(args.mem0);
#pragma unroll
        for (int i = 0; i < 8; i++) {
          const int d = (i >> 2) * 256 + warp * 32 + (i & 3) * 8 + g;
          pk[i] = (uint32_t)m0[(2 * t) * DM + d] | ((uint32_t)m0[(2 * t + 1) * DM + d] << 16);
        }
      } else {
        const uint8_t* p = ring_l + ((s - 1) & 3) * RING_SLOT;
        uint4 a0, a1; uint32_t b0, b1;
        int it = 0;
        while (true) {
          a0 = ldv128(p); a1 = ldv128(p + 10240); b0 = ldv32(p + ring_s); b1 = ldv32(p + ring_s + 10240);
          const bool ok = ((a0.w & a1.w & b0 & b1) >> 16) == 0x5000u;
          if (__all_sync(~0u, ok)) break;
          if (++it > SPIN_LIMIT) { g_err = 3; break; }
        }
        const float sc = __uint_as_float(lds32(sb + C_SC));
        a0.w = __byte_perm(a0.w, b0, 0x5410); a1.w = __byte_perm(a1.w, b1, 0x5410);
        float2 f;
        f = unpack_f16(a0.x); pk[0] = pack_bf16(f.x * sc, f.y * sc);
        f = unpack_f16(a0.y); pk[1] = pack_bf16(f.x * sc, f.y * sc);
        f = unpack_f16(a0.z); pk[2] = pack_bf16(f.x * sc, f.y * sc);
        f = unpack_f16(a0.w); pk[3] = pack_bf16(f.x * sc, f.y * sc);
        f = unpack_f16(a1.x); pk[4] = pack_bf16(f.x * sc, f.y * sc);
        f = unpack_f16(a1.y); pk[5] = pack_bf16(f.x * sc, f.y * sc);
        f = unpack_f16(a1.z); pk[6] = pack_bf16(f.x * sc, f.y * sc);
        f = unpack_f16(a1.w); pk[7] = pack_bf16(f.x * sc, f.y * sc);
      }
      STAMP(0);
      stm4(mem_st, pk[0], pk[1], pk[2], pk[3]);
      stm4(mem_st + 4096, pk[4], pk[5], pk[6], pk[7]);
      bar_sync<1, 256>();
      STAMP(1);
      const uint32_t qb = qm_st + (s & 1) * QM_BUF;
      const uint32_t pm = sb + MB_PEER + (s & 1) * 8 + peer_d;
      float c0[4], c1[4], cv[4];
      {
        uint32_t b[4];
        ldm4t(b, mem_ld0);
        uint32_t m = absmax2(absmax2(absmax2(pk[0], pk[1]), absmax2(pk[2], pk[3])), absmax2(absmax2(pk[4], pk[5]), absmax2(pk[6], pk[7])));
        m = __reduce_max_sync(~0u, fold_absmax(m));
        if (lane == 0) sts32(sb + C_MX + warp * 4, m);
        mma16z(c0, wa[0][0], wa[0][1], wa[0][2], wa[0][3], b[0], b[1]);
        mma16z(cv, R[0][0], R[0][1], R[0][2], R[0][3], b[0], b[1]);
        mma16z(c1, wa[1][0], wa[1][1], wa[1][2], wa[1][3], b[2], b[3]);
        mma16(cv, R[1][0], R[1][1], R[1][2], R[1][3], b[2], b[3]);
      }
#pragma unroll
      for (int i = 2; i < 16; i += 2) {
        uint32_t b[4];
        ldm4t(b, mem_ld0 + i * 256);
        mma16(c0, wa[i][0], wa[i][1], wa[i][2], wa[i][3], b[0], b[1]);
        mma16(cv, R[i][0], R[i][1], R[i][2], R[i][3], b[0], b[1]);
        mma16(c1, wa[i + 1][0], wa[i + 1][1], wa[i + 1][2], wa[i + 1][3], b[2], b[3]);
        mma16(cv, R[i + 1][0], R[i + 1][1], R[i + 1][2], R[i + 1][3], b[2], b[3]);
      }
#pragma unroll
      for (int i = 16; i < 32; i += 2) {
        uint32_t b[4];
        ldm4t(b, mem_ld1 + (i - 16) * 256);
        mma16(c0, wa[i][0], wa[i][1], wa[i][2], wa[i][3], b[0], b[1]);
        mma16(c1, wa[i + 1][0], wa[i + 1][1], wa[i + 1][2], wa[i + 1][3], b[2], b[3]);
        if (i == 18) sts64f(vp_st, gam ? cv[0] : cv[2], gam ? cv[1] : cv[3]);
        if (i == 24) {
          bar_sync_id(2 + w, 64);
          const float2 o = lds64f(vp_st ^ 256);
          const uint32_t v = pack_bf16((gam ? cv[2] : cv[0]) + o.x, (gam ? cv[3] : cv[1]) + o.y);
          const uint32_t a = (qb ^ (gam << 5)) + 4096;
          st_async32(a + peer_d, v, pm);
          sts32(a, v);
        }
      }
      {
        const uint32_t lo = pack_bf16(c0[0] + c1[0], c0[1] + c1[1]), hi = pack_bf16(c0[2] + c1[2], c0[3] + c1[3]);
        const uint32_t a = qb + gam * 2048;
        st_async32(a + peer_d, lo, pm);
        st_async32((a ^ 32) + peer_d, hi, pm);
        sts32(a, lo);
        sts32(a ^ 32, hi);
      }
      bar_arrive<6, 384>();
      STAMP(2);
      if (s == NSEG - 1) break;
      if (s == 0) mbar_wait(sb + MB_WO, 0);
#pragma unroll
      for (int i = 0; i < 16; i++) ldm4t(R[i], (wo_a ^ ((i & 1) << 5)) + ((i >> 1) << 11));
      bar_sync<7, 384>();
      STAMP(3);
      {
        uint32_t b[4][4];
#pragma unroll
        for (int i = 0; i < 4; i++) ldm4t(b[i], ot_ld + i * 512);
        mma16z(c0, R[0][0], R[0][1], R[0][2], R[0][3], b[0][0], b[0][1]);
        mma16z(c1, R[1][0], R[1][1], R[1][2], R[1][3], b[0][0], b[0][1]);
#pragma unroll
        for (int k = 1; k < 8; k++) {
          mma16(c0, R[2 * k][0], R[2 * k][1], R[2 * k][2], R[2 * k][3], b[k >> 1][(k & 1) * 2], b[k >> 1][(k & 1) * 2 + 1]);
          mma16(c1, R[2 * k + 1][0], R[2 * k + 1][1], R[2 * k + 1][2], R[2 * k + 1][3], b[k >> 1][(k & 1) * 2], b[k >> 1][(k & 1) * 2 + 1]);
        }
      }
      {
        uint8_t* p = ring_l + (s & 3) * RING_SLOT + j * 10240;
        asm volatile("red.relaxed.gpu.global.add.noftz.v4.f16x2 [%0], {%1,%2,%3,%4};"
                     :: "l"(p), "r"(pack_f16(c0[0], c0[1])), "r"(pack_f16(c0[2], c0[3])), "r"(pack_f16(c1[0], c1[1])), "r"(pack_f16(c1[2], 1.0f)) : "memory");
        asm volatile("red.relaxed.gpu.global.add.noftz.f16x2 [%0], %1;" :: "l"(p + ring_s), "r"(pack_f16(c1[3], 1.0f)) : "memory");
      }
      bar_arrive<9, 384>();
      STAMP(4);
#pragma unroll
      for (int i = 0; i < 16; i++) ldm4t(R[i], wv_a + (i << 11));
      STAMP(5);
    }
  } else {
    asm volatile("setmaxnreg.dec.sync.aligned.u32 56;");
    const int w = warp - 8, at = tid - 256;
    {
      uint32_t mx = 0, mo = 0;
      const uint4 gw0 = __ldg(reinterpret_cast<const uint4*>(args.gate_w) + lane), gw1 = __ldg(reinterpret_cast<const uint4*>(args.gate_w) + 32 + lane);
      for (int r = 0; r < 8; r++) {
        const int tok = cta * SEGL + w * 8 + r;
        const uint4* xr = reinterpret_cast<const uint4*>(args.x + (size_t)tok * DM);
        const uint4 a = __ldg(xr + lane), b = __ldg(xr + 32 + lane);
        float acc = bf_lo(a.x) * bf_lo(gw0.x) + bf_hi(a.x) * bf_hi(gw0.x) + bf_lo(a.y) * bf_lo(gw0.y) + bf_hi(a.y) * bf_hi(gw0.y) +
                    bf_lo(a.z) * bf_lo(gw0.z) + bf_hi(a.z) * bf_hi(gw0.z) + bf_lo(a.w) * bf_lo(gw0.w) + bf_hi(a.w) * bf_hi(gw0.w) +
                    bf_lo(b.x) * bf_lo(gw1.x) + bf_hi(b.x) * bf_hi(gw1.x) + bf_lo(b.y) * bf_lo(gw1.y) + bf_hi(b.y) * bf_hi(gw1.y) +
                    bf_lo(b.z) * bf_lo(gw1.z) + bf_hi(b.z) * bf_hi(gw1.z) + bf_lo(b.w) * bf_lo(gw1.w) + bf_hi(b.w) * bf_hi(gw1.w);
        mx = absmax2(absmax2(mx, absmax2(absmax2(a.x, a.y), absmax2(a.z, a.w))), absmax2(absmax2(b.x, b.y), absmax2(b.z, b.w)));
#pragma unroll
        for (int o = 16; o; o >>= 1) acc += __shfl_xor_sync(~0u, acc, o);
        if (lane == 0) g_gate[tok] = 1.0f / (1.0f + __expf(-acc));
      }
      const uint4* wr = reinterpret_cast<const uint4*>(args.wo + (size_t)(h * DH + w * 32) * DM + j * 256) + lane;
#pragma unroll 8
      for (int r = 0; r < 32; r++) {
        const uint4 a = __ldg(wr + r * (DM / 8));
        mo = absmax2(mo, absmax2(absmax2(a.x, a.y), absmax2(a.z, a.w)));
      }
      mx = __reduce_max_sync(~0u, fold_absmax(mx));
      mo = __reduce_max_sync(~0u, fold_absmax(mo));
      if (lane == 0) { sts32(sb + C_WM + 32 + w * 4, mx); sts32(sb + C_WM + 48 + w * 4, mo); }
      __threadfence();
    }
    bar_sync<10, 384>();
    const uint8_t* blk = g_qkv + (size_t)h * BLK_BYTES;
    if (at == 0) {
      mbar_expect_tx(sb + MB_WO, 65536);
      for (int i = 0; i < 4; i++) tma2d(sb + C_WO + i * 16384, &tmo, j * 256 + i * 64, h * DH, sb + MB_WO);
      for (int i = 0; i < 3; i++) {
        const uint8_t* src = blk + (size_t)i * NH * BLK_BYTES;
        mbar_expect_tx(sb + MB_KVQ + 8 * i, KVQ_ST);
        bulk_g2s(sb + C_KVQ + i * KVQ_ST, src, 16384, sb + MB_KVQ + 8 * i);
        bulk_g2s(sb + C_KVQ + i * KVQ_ST + 16384, src + 16384 + j * 4096, 4096, sb + MB_KVQ + 8 * i);
      }
    }
    bar_sync<11, 384>();
    int wexp;
    {
      if (at == 0) {
        const uint4 a = lds128(sb + C_WM), b = lds128(sb + C_WM + 16), c = lds128(sb + C_WM + 32), d = lds128(sb + C_WM + 48);
        uint4 r;
        r.x = tag;
        r.y = max(max(c.x, c.y), max(c.z, c.w)) >> 7;
        r.z = max(max(max(a.x, a.y), max(a.z, a.w)), max(max(b.x, b.y), max(b.z, b.w))) >> 7;
        r.w = max(max(d.x, d.y), max(d.z, d.w)) >> 7;
        asm volatile("st.volatile.global.v4.u32 [%0], {%1,%2,%3,%4};" :: "l"(&g_pub[cta]), "r"(r.x), "r"(r.y), "r"(r.z), "r"(r.w) : "memory");
      }
      uint4 r0, r1;
      int it = 0;
      while (true) {
        r0 = ldv128(&g_pub[lane]); r1 = ldv128(&g_pub[lane + 32]);
        if (__all_sync(~0u, r0.x == tag && r1.x == tag)) break;
        if (++it > SPIN_LIMIT) { g_err = 4; break; }
      }
      __threadfence();
      if (w == 0) { sts32(sb + C_XE + lane * 4, r0.y); sts32(sb + C_XE + 128 + lane * 4, r1.y); }
      wexp = (int)__reduce_max_sync(~0u, max(r0.z, r1.z)) + (int)__reduce_max_sync(~0u, max(r0.w, r1.w)) - 3 * 126 + 21 - 14;
      bar_sync<8, 128>();
    }
    const uint32_t swl = (lane ^ (((lane >> 3) & 3) << 1)) * 16;
    const uint32_t k_l = (8 * w + (lane & 7)) * 256 + (((lane >> 3) ^ (lane & 7)) << 4);
    const uint32_t v_l = 8192 + ((lane & 7) + ((lane >> 4) << 3)) * 256 + (w >> 1) * 128 + ((((w & 1) * 4 + ((lane >> 3) & 1)) ^ (lane & 7)) << 4);
    const uint32_t ot_st = sb + C_OT + (32 * w + 8 * ((lane & 7) >> 1) + ((2 * (lane >> 3)) ^ (lane & 6)) + (lane & 1)) * 16;
    const float SC = 0.08838834764831845f * 1.4426950408889634f;
    int st = 0, stp = 0;
    for (int s = 0; s < NSEG; s++) {
      const uint32_t kv = sb + C_KVQ + st * KVQ_ST;
      const uint32_t qm = sb + C_QM + (s & 1) * QM_BUF + swl;
      mbar_wait(sb + MB_KVQ + 8 * st, stp);
      if (s < NSEG - 1) {
        uint32_t kb[4][4], va[4][4];
        ldm4(kb[0], kv + k_l + j * 128); ldm4(kb[1], kv + (k_l ^ 64) + j * 128);
        ldm4(kb[2], kv + k_l + (j ^ 1) * 128); ldm4(kb[3], kv + (k_l ^ 64) + (j ^ 1) * 128);
        ldm4t(va[0], kv + v_l); ldm4t(va[1], kv + v_l + 4096); ldm4t(va[2], kv + (v_l ^ 32)); ldm4t(va[3], kv + (v_l ^ 32) + 4096);
        const int xe = (int)lds32(sb + C_XE + s * 4);
        bar_sync<6, 384>();
        STAMP(8);
        float sx0[4], sx1[4], sm0[4], sm1[4];
        uint32_t q0[4], q1[4], k0[4], k1[4];
        ldm4t(q0, qm + j * 1024); ldm4t(k0, qm + 2048 + j * 1024); ldm4t(q1, qm + j * 1024 + 512); ldm4t(k1, qm + 2048 + j * 1024 + 512);
        const uint4 ma = lds128(sb + C_MX), mb = lds128(sb + C_MX + 16);
        mma16z(sx0, q0[0], 0, q0[1], 0, kb[0][0], kb[0][1]); mma16z(sm0, q0[0], 0, q0[1], 0, k0[0], k0[1]);
        mma16z(sx1, q0[2], 0, q0[3], 0, kb[0][2], kb[0][3]); mma16z(sm1, q0[2], 0, q0[3], 0, k0[2], k0[3]);
        mma16(sx0, q1[0], 0, q1[1], 0, kb[1][0], kb[1][1]); mma16(sm0, q1[0], 0, q1[1], 0, k1[0], k1[1]);
        mma16(sx1, q1[2], 0, q1[3], 0, kb[1][2], kb[1][3]); mma16(sm1, q1[2], 0, q1[3], 0, k1[2], k1[3]);
        int E = max((int)(max(max(max(ma.x, ma.y), max(ma.z, ma.w)), max(max(mb.x, mb.y), max(mb.z, mb.w))) >> 7), xe) + wexp;
        E = min(max(E, -100), 100);
        mbar_wait_cluster(sb + MB_PEER + (s & 1) * 8, (s >> 1) & 1);
        STAMP(9);
        uint32_t vm[4];
        ldm4t(q0, qm + (j ^ 1) * 1024); ldm4t(q1, qm + (j ^ 1) * 1024 + 512);
        ldm4t(k0, qm + 2048 + (j ^ 1) * 1024); ldm4t(k1, qm + 2048 + (j ^ 1) * 1024 + 512);
        ldm4(vm, qm + 4096 + w * 512);
        mma16(sx0, q0[0], 0, q0[1], 0, kb[2][0], kb[2][1]); mma16(sx1, q0[2], 0, q0[3], 0, kb[2][2], kb[2][3]);
        mma16(sx0, q1[0], 0, q1[1], 0, kb[3][0], kb[3][1]); mma16(sx1, q1[2], 0, q1[3], 0, kb[3][2], kb[3][3]);
        mma16(sm0, q0[0], 0, q0[1], 0, k0[0], k0[1]); mma16(sm1, q0[2], 0, q0[3], 0, k0[2], k0[3]);
        mma16(sm0, q1[0], 0, q1[1], 0, k1[0], k1[1]); mma16(sm1, q1[2], 0, q1[3], 0, k1[2], k1[3]);
        sts64f(sb + C_SX + w * 256 + lane * 8, sx0[0] + sx1[0], sx0[1] + sx1[1]);
        bar_sync<8, 128>();
        float2 sv[5];
#pragma unroll
        for (int i = 0; i < 4; i++) sv[i] = lds64f(sb + C_SX + i * 256 + lane * 8);
        sv[4] = make_float2(sm0[0] + sm1[0], sm0[1] + sm1[1]);
        float m = fmaxf(fmaxf(fmaxf(sv[0].x, sv[0].y), fmaxf(sv[1].x, sv[1].y)), fmaxf(fmaxf(sv[2].x, sv[2].y), fmaxf(sv[3].x, sv[3].y)));
        m = fmaxf(m, fmaxf(sv[4].x, sv[4].y));
        m = fmaxf(m, __shfl_xor_sync(~0u, m, 1));
        m = fmaxf(m, __shfl_xor_sync(~0u, m, 2));
        m *= -SC;
        uint32_t p[5];
#pragma unroll
        for (int i = 0; i < 5; i++) p[i] = pack_bf16(ex2(fmaf(sv[i].x, SC, m)), ex2(fmaf(sv[i].y, SC, m)));
        float o0[4], o1[4], su[4];
        const uint32_t ONE = 0x3F803F80u;
        mma16z(su, ONE, ONE, ONE, ONE, p[0], p[1]);
        mma16z(o0, va[0][0], va[0][1], va[0][2], va[0][3], p[0], p[1]);
        mma16z(o1, va[2][0], va[2][1], va[2][2], va[2][3], p[0], p[1]);
        mma16(su, ONE, ONE, ONE, ONE, p[2], p[3]);
        mma16(o0, va[1][0], va[1][1], va[1][2], va[1][3], p[2], p[3]);
        mma16(o1, va[3][0], va[3][1], va[3][2], va[3][3], p[2], p[3]);
        mma8(su, ONE, ONE, p[4]);
        mma8(o0, vm[0], vm[1], p[4]);
        mma8(o1, vm[2], vm[3], p[4]);
        const float dn = __uint_as_float((uint32_t)(127 - E) << 23);
        const float r0 = __fdividef(dn, su[0]), r1 = __fdividef(dn, su[1]);
        stm4(ot_st, pack_bf16(o0[0] * r0, o0[1] * r1), pack_bf16(o0[2] * r0, o0[3] * r1), pack_bf16(o1[0] * r0, o1[1] * r1), pack_bf16(o1[2] * r0, o1[3] * r1));
        if (at == 0) sts32(sb + C_SC, (uint32_t)(127 + E) << 23);
        bar_arrive<7, 384>();
        STAMP(10);
        if (at == 0) mbar_expect_tx(sb + MB_PEER + (s & 1) * 8, 3072);
        if (w == 1 && lane < 10) {
          const int u = cta * 10 + lane;
          *reinterpret_cast<uint4*>(g_ring + ((s + 2) & 3) * RING_SLOT + (u >> 3) * 256 + (u & 7) * 16) = make_uint4(0, 0, 0, 0);
          __threadfence();
        }
        bar_sync<9, 384>();
      } else {
        bar_sync<6, 384>();
        mbar_wait_cluster(sb + MB_PEER + (s & 1) * 8, (s >> 1) & 1);
        if (w == 1 && lane < 10) {
          const int u = cta * 10 + lane;
          *reinterpret_cast<uint4*>(g_ring + ((s + 2) & 3) * RING_SLOT + (u >> 3) * 256 + (u & 7) * 16) = make_uint4(0, 0, 0, 0);
        }
      }
      STAMP(11);
      {
        const int tok = s * SEGL + 16 * j + g;
        const float g0 = __ldcg(&g_gate[tok]), g1 = __ldcg(&g_gate[tok + 8]);
        float sc[5][4];
#pragma unroll
        for (int i = 0; i < 5; i++) sc[i][0] = sc[i][1] = sc[i][2] = sc[i][3] = 0.f;
        const uint32_t q_l = kv + 16384 + (lane & 15) * 256;
        const uint32_t kx_l = kv + ((lane & 7) + ((lane >> 4) << 3)) * 256;
#pragma unroll
        for (int i = 0; i < 4; i++) {
          uint32_t km[4];
          ldm4t(km, qm + 2048 + i * 512);
#pragma unroll
          for (int u = 0; u < 2; u++) {
            const int ks = 2 * i + u;
            uint32_t a[4], b[4];
            ldm4(a, q_l + (((2 * ks + (lane >> 4)) ^ (lane & 7)) << 4));
            const uint32_t co = ((2 * ks + ((lane >> 3) & 1)) ^ (lane & 7)) << 4;
            ldm4(b, kx_l + co);
            mma16(sc[0], a[0], a[1], a[2], a[3], b[0], b[1]);
            mma16(sc[1], a[0], a[1], a[2], a[3], b[2], b[3]);
            ldm4(b, kx_l + 4096 + co);
            mma16(sc[2], a[0], a[1], a[2], a[3], b[0], b[1]);
            mma16(sc[3], a[0], a[1], a[2], a[3], b[2], b[3]);
            mma16(sc[4], a[0], a[1], a[2], a[3], km[2 * u], km[2 * u + 1]);
          }
        }
        const float NEG = -1.0e9f * 1.4426950408889634f;
        const int r = 16 * j + g;
        float m0 = -INFINITY, m1 = -INFINITY;
#pragma unroll
        for (int i = 0; i < 5; i++) {
          const int key = (i < 4) ? 8 * i + 2 * t : -2;
          sc[i][0] = key <= r ? sc[i][0] * SC : NEG;
          sc[i][1] = key + 1 <= r ? sc[i][1] * SC : NEG;
          sc[i][2] = key <= r + 8 ? sc[i][2] * SC : NEG;
          sc[i][3] = key + 1 <= r + 8 ? sc[i][3] * SC : NEG;
          m0 = fmaxf(m0, fmaxf(sc[i][0], sc[i][1]));
          m1 = fmaxf(m1, fmaxf(sc[i][2], sc[i][3]));
        }
        m0 = fmaxf(m0, __shfl_xor_sync(~0u, m0, 1)); m0 = fmaxf(m0, __shfl_xor_sync(~0u, m0, 2));
        m1 = fmaxf(m1, __shfl_xor_sync(~0u, m1, 1)); m1 = fmaxf(m1, __shfl_xor_sync(~0u, m1, 2));
        float s0 = 0.f, s1 = 0.f;
        uint32_t p[5][2];
#pragma unroll
        for (int i = 0; i < 5; i++) {
          const float e0 = ex2(sc[i][0] - m0), e1 = ex2(sc[i][1] - m0), e2 = ex2(sc[i][2] - m1), e3 = ex2(sc[i][3] - m1);
          s0 += e0 + e1; s1 += e2 + e3;
          p[i][0] = pack_bf16(e0, e1); p[i][1] = pack_bf16(e2, e3);
        }
        s0 += __shfl_xor_sync(~0u, s0, 1); s0 += __shfl_xor_sync(~0u, s0, 2);
        s1 += __shfl_xor_sync(~0u, s1, 1); s1 += __shfl_xor_sync(~0u, s1, 2);
        uint32_t vm[4];
        ldm4(vm, qm + 4096 + w * 512);
        float o[4][4];
        const uint32_t vx_l = kv + 8192 + lane * 256 + (w >> 1) * 128;
#pragma unroll
        for (int i = 0; i < 4; i++) {
          uint32_t b[4];
          ldm4t(b, vx_l + ((((w & 1) * 4 + i) ^ (lane & 7)) << 4));
          mma8z(o[i], p[4][0], p[4][1], vm[i]);
          mma16(o[i], p[0][0], p[0][1], p[1][0], p[1][1], b[0], b[1]);
          mma16(o[i], p[2][0], p[2][1], p[3][0], p[3][1], b[2], b[3]);
        }
        const float r0 = __fdividef(g0, s0), r1 = __fdividef(g1, s1);
        bf16* op = g_o + (size_t)tok * HD + h * DH + 32 * w + 8 * t;
        *reinterpret_cast<uint4*>(op) = make_uint4(pack_bf16(o[0][0] * r0, o[0][1] * r0), pack_bf16(o[1][0] * r0, o[1][1] * r0),
                                                   pack_bf16(o[2][0] * r0, o[2][1] * r0), pack_bf16(o[3][0] * r0, o[3][1] * r0));
        *reinterpret_cast<uint4*>(op + 8 * HD) = make_uint4(pack_bf16(o[0][2] * r1, o[0][3] * r1), pack_bf16(o[1][2] * r1, o[1][3] * r1),
                                                            pack_bf16(o[2][2] * r1, o[2][3] * r1), pack_bf16(o[3][2] * r1, o[3][3] * r1));
      }
      bar_sync<8, 128>();
      STAMP(12);
      if (at == 0 && s + 3 < NSEG) {
        const uint8_t* src = blk + (size_t)(s + 3) * NH * BLK_BYTES;
        mbar_expect_tx(sb + MB_KVQ + 8 * st, KVQ_ST);
        bulk_g2s(kv, src, 16384, sb + MB_KVQ + 8 * st);
        bulk_g2s(kv + 16384, src + 16384 + j * 4096, 4096, sb + MB_KVQ + 8 * st);
      }
      if (++st == 3) { st = 0; stp ^= 1; }
    }
    if (at == 0) atomicAdd(&g_done, 1u);
  }
}

template <int MODE>
__global__ void __launch_bounds__(256) simple_gemm(const bf16* A, int lda, const bf16* B, const bf16* B2, int ldb, int K, int which, bf16* out) {
  __shared__ float As[16][68], Bs[16][68], Bs2[16][68];
  const int tx = threadIdx.x & 15, ty = threadIdx.x >> 4;
  const int m0 = blockIdx.y * 64, n0 = blockIdx.x * 64;
  float acc[4][4] = {}, acc2[4][4] = {};
  const int KT = (MODE == 2) ? HD + FF : K;
  for (int k0 = 0; k0 < KT; k0 += 16) {
    for (int i = threadIdx.x; i < 1024; i += 256) {
      const int r = i >> 4, c = i & 15;
      float v;
      if (MODE == 2) v = __bfloat162float(k0 < HD ? g_o[(size_t)(m0 + r) * HD + k0 + c] : g_h[(size_t)(m0 + r) * FF + k0 - HD + c]);
      else v = __bfloat162float(A[(size_t)(m0 + r) * lda + k0 + c]);
      As[c][r] = v;
      const int kr = i >> 6, nc = i & 63;
      if (MODE == 2) Bs[kr][nc] = __bfloat162float(k0 < HD ? B[(size_t)(k0 + kr) * ldb + n0 + nc] : B2[(size_t)(k0 - HD + kr) * ldb + n0 + nc]);
      else Bs[kr][nc] = __bfloat162float(B[(size_t)(k0 + kr) * ldb + n0 + nc]);
      if (MODE == 1) Bs2[kr][nc] = __bfloat162float(B2[(size_t)(k0 + kr) * ldb + n0 + nc]);
    }
    __syncthreads();
#pragma unroll
    for (int k = 0; k < 16; k++) {
      float a[4], b[4], b2[4];
#pragma unroll
      for (int i = 0; i < 4; i++) { a[i] = As[k][ty * 4 + i]; b[i] = Bs[k][tx * 4 + i]; b2[i] = MODE == 1 ? Bs2[k][tx * 4 + i] : 0.f; }
#pragma unroll
      for (int i = 0; i < 4; i++)
#pragma unroll
        for (int l = 0; l < 4; l++) { acc[i][l] += a[i] * b[l]; if (MODE == 1) acc2[i][l] += a[i] * b2[l]; }
    }
    __syncthreads();
  }
#pragma unroll
  for (int i = 0; i < 4; i++)
#pragma unroll
    for (int l = 0; l < 4; l++) {
      const int m = m0 + ty * 4 + i, n = n0 + tx * 4 + l;
      if (MODE == 0) {
        const int seg = m >> 5, row = m & 31, hh = n >> 7, e = n & 127;
        const int p = (e & 96) | (((e >> 1) & 3) << 3) | (((e >> 3) & 3) << 1) | (e & 1);
        bf16* dst = reinterpret_cast<bf16*>(g_qkv + ((size_t)seg * NH + hh) * BLK_BYTES + which * 8192 + row * 256 + (((p >> 3) ^ (row & 7)) << 4) + (p & 7) * 2);
        *dst = __float2bfloat16(acc[i][l]);
      } else if (MODE == 1) {
        g_h[(size_t)m * FF + n] = __float2bfloat16(acc2[i][l] / (1.0f + __expf(-acc[i][l])) * (1.0f - g_gate[m]));
      } else {
        out[(size_t)m * DM + n] = __float2bfloat16(acc[i][l]);
      }
    }
}
__global__ void clear_ring() { reinterpret_cast<uint4*>(g_ring)[blockIdx.x * 256 + threadIdx.x] = make_uint4(0, 0, 0, 0); }

typedef CUresult (*EncodeFn)(CUtensorMap*, CUtensorMapDataType, cuuint32_t, void*, const cuuint64_t*, const cuuint64_t*, const cuuint32_t*,
                             const cuuint32_t*, CUtensorMapInterleave, CUtensorMapSwizzle, CUtensorMapL2promotion, CUtensorMapFloatOOBfill);
static void make_map(EncodeFn enc, CUtensorMap* tm, const void* base, uint64_t cols, uint64_t rows, uint32_t bc, uint32_t br) {
  cuuint64_t dims[2] = {cols, rows};
  cuuint64_t strides[1] = {cols * 2};
  cuuint32_t box[2] = {bc, br}, es[2] = {1, 1};
  enc(tm, CU_TENSOR_MAP_DATA_TYPE_BFLOAT16, 2, const_cast<void*>(base), dims, strides, box, es, CU_TENSOR_MAP_INTERLEAVE_NONE,
      CU_TENSOR_MAP_SWIZZLE_128B, CU_TENSOR_MAP_L2_PROMOTION_L2_256B, CU_TENSOR_MAP_FLOAT_OOB_FILL_NONE);
}

extern "C" void kernel_launch(void* const* d_in, const int* in_sizes, int n_in, void* d_out, int out_size) {
  (void)in_sizes; (void)n_in; (void)out_size;
  const bf16 *x = (const bf16*)d_in[0], *mem0 = (const bf16*)d_in[1], *wq = (const bf16*)d_in[2], *wk = (const bf16*)d_in[3],
             *wv = (const bf16*)d_in[4], *wo = (const bf16*)d_in[5], *wg = (const bf16*)d_in[8], *wu = (const bf16*)d_in[9],
             *wd = (const bf16*)d_in[10], *gw = (const bf16*)d_in[11];
  static EncodeFn enc = nullptr;
  if (!enc) {
    void* fn = nullptr; cudaDriverEntryPointQueryResult qr;
    cudaGetDriverEntryPoint("cuTensorMapEncodeTiled", &fn, cudaEnableDefault, &qr);
    enc = (EncodeFn)fn;
    cudaFuncSetAttribute(chain_kernel, cudaFuncAttributeMaxDynamicSharedMemorySize, C_SMEM);
  }
  CUtensorMap tmq, tmk, tmv, tmo;
  make_map(enc, &tmq, wq, HD, DM, 64, 256); make_map(enc, &tmk, wk, HD, DM, 64, 256); make_map(enc, &tmv, wv, HD, DM, 64, 256);
  make_map(enc, &tmo, wo, DM, HD, 64, 128);
  cudaStream_t st = cudaStreamPerThread;
  clear_ring<<<4 * RING_SLOT / 4096, 256, 0, st>>>();
  simple_gemm<0><<<dim3(HD / 64, SEQ / 64), 256, 0, st>>>(x, DM, wk, nullptr, HD, DM, 0, nullptr);
  simple_gemm<0><<<dim3(HD / 64, SEQ / 64), 256, 0, st>>>(x, DM, wv, nullptr, HD, DM, 1, nullptr);
  simple_gemm<0><<<dim3(HD / 64, SEQ / 64), 256, 0, st>>>(x, DM, wq, nullptr, HD, DM, 2, nullptr);
  {
    cudaLaunchConfig_t cfg = {};
    cfg.gridDim = dim3(64); cfg.blockDim = dim3(384); cfg.dynamicSmemBytes = C_SMEM; cfg.stream = st;
    cudaLaunchAttribute at[1];
    at[0].id = cudaLaunchAttributeClusterDimension; at[0].val.clusterDim.x = 2; at[0].val.clusterDim.y = 1; at[0].val.clusterDim.z = 1;
    cfg.attrs = at; cfg.numAttrs = 1;
    ChainArgs ca{x, mem0, wo, gw};
    cudaLaunchKernelEx(&cfg, chain_kernel, tmq, tmk, tmv, tmo, ca);
  }
  simple_gemm<1><<<dim3(FF / 64, SEQ / 64), 256, 0, st>>>(x, DM, wg, wu, FF, DM, 0, nullptr);
  simple_gemm<2><<<dim3(DM / 64, SEQ / 64), 256, 0, st>>>(nullptr, 0, wo, wd, DM, 0, 0, (bf16*)d_out);
}
```

```cpp
#include <cuda_runtime.h>
#include <cuda_bf16.h>
#include <cuda_fp16.h>
#include <cuda.h>
#include <stdint.h>

typedef __nv_bfloat16 bf16;
#define FAT_REGS "224"
#define AUX_REGS "56"
#define WO_IN 2
#define WO_EARLY 10
#define WV_A 8
#define POLL_DELAY 8

constexpr int SEQ = 2048, DM = 512, NH = 32, DH = 128, SEGL = 32, NSEG = 64, FF = 1792;
constexpr int HD = NH * DH;
constexpr int KA = HD + FF;
constexpr int NCTA = 132, NGC = 34, MAXJOBS = 320;
constexpr int BLK_BYTES = 24576;
constexpr int RING_SLOT = 80 * 256;
constexpr int SPIN_LIMIT = 1 << 20;

__device__ __align__(1024) uint8_t g_qkv[(size_t)NSEG * NH * BLK_BYTES];
__device__ __align__(1024) bf16 g_a[(size_t)SEQ * KA];
__device__ __align__(1024) float g_acc[(size_t)SEQ * DM];
__device__ unsigned g_fq[NSEG * NH];
__device__ unsigned g_fh[128];
__device__ unsigned g_fo[128];
__device__ unsigned g_fc[256];
__device__ __align__(1024) uint8_t g_ring[8 * RING_SLOT];
__device__ __align__(128) float g_gate[SEQ];
__device__ uint4 g_pub[64];
__device__ unsigned g_done;
__device__ int g_err;

__device__ __forceinline__ uint32_t smem_u32(const void* p) { return (uint32_t)__cvta_generic_to_shared(p); }
__device__ __forceinline__ uint32_t mapa(uint32_t a, uint32_t rank) { uint32_t r; asm volatile("mapa.shared::cluster.u32 %0, %1, %2;" : "=r"(r) : "r"(a), "r"(rank)); return r; }
__device__ __forceinline__ void mbar_init(uint32_t a, uint32_t cnt) { asm volatile("mbarrier.init.shared::cta.b64 [%0], %1;" :: "r"(a), "r"(cnt) : "memory"); }
__device__ __forceinline__ void mbar_expect_tx(uint32_t a, uint32_t bytes) { asm volatile("mbarrier.arrive.expect_tx.shared::cta.b64 _, [%0], %1;" :: "r"(a), "r"(bytes) : "memory"); }
__device__ __forceinline__ bool mbar_try(uint32_t a, uint32_t parity) {
  uint32_t ok;
  asm volatile("{ .reg .pred p; mbarrier.try_wait.parity.shared::cta.b64 p, [%1], %2; selp.u32 %0, 1, 0, p; }" : "=r"(ok) : "r"(a), "r"(parity) : "memory");
  return ok;
}
__device__ __forceinline__ bool mbar_try_cluster(uint32_t a, uint32_t parity) {
  uint32_t ok;
  asm volatile("{ .reg .pred p; mbarrier.try_wait.parity.acquire.cluster.shared::cta.b64 p, [%1], %2; selp.u32 %0, 1, 0, p; }" : "=r"(ok) : "r"(a), "r"(parity) : "memory");
  return ok;
}
__device__ __forceinline__ bool give_up(int it, int code) {
  if ((it & 1023) != 0) return false;
  if (it < SPIN_LIMIT && *reinterpret_cast<volatile int*>(&g_err) == 0) return false;
  if (it >= SPIN_LIMIT) g_err = code;
  return true;
}
__device__ __forceinline__ void mbar_wait(uint32_t a, uint32_t parity) {
  int it = 0;
  while (!mbar_try(a, parity)) { if (give_up(++it, 1)) break; }
}
__device__ __forceinline__ void mbar_wait_cluster(uint32_t a, uint32_t parity) {
  int it = 0;
  while (!mbar_try_cluster(a, parity)) { if (give_up(++it, 2)) break; }
}
template <int ID, int N> __device__ __forceinline__ void bar_sync() { asm volatile("bar.sync %0, %1;" :: "n"(ID), "n"(N) : "memory"); }
template <int ID, int N> __device__ __forceinline__ void bar_arrive() { asm volatile("bar.arrive %0, %1;" :: "n"(ID), "n"(N) : "memory"); }
__device__ __forceinline__ void bar_sync_id(int id, int n) { asm volatile("bar.sync %0, %1;" :: "r"(id), "r"(n) : "memory"); }
__device__ __forceinline__ void tma2d(uint32_t dst, const CUtensorMap* tm, int c0, int c1, uint32_t mb) {
  asm volatile("cp.async.bulk.tensor.2d.shared::cluster.global.mbarrier::complete_tx::bytes [%0], [%1, {%3, %4}], [%2];"
               :: "r"(dst), "l"((uint64_t)tm), "r"(mb), "r"(c0), "r"(c1) : "memory");
}
__device__ __forceinline__ void bulk_g2s(uint32_t dst, const void* src, uint32_t bytes, uint32_t mb) {
  asm volatile("cp.async.bulk.shared::cluster.global.mbarrier::complete_tx::bytes [%0], [%1], %2, [%3];"
               :: "r"(dst), "l"(src), "r"(bytes), "r"(mb) : "memory");
}
__device__ __forceinline__ void ldm4(uint32_t* r, uint32_t a) {
  asm volatile("ldmatrix.sync.aligned.m8n8.x4.shared.b16 {%0,%1,%2,%3}, [%4];" : "=r"(r[0]), "=r"(r[1]), "=r"(r[2]), "=r"(r[3]) : "r"(a) : "memory");
}
__device__ __forceinline__ void ldm4t(uint32_t* r, uint32_t a) {
  asm volatile("ldmatrix.sync.aligned.m8n8.x4.trans.shared.b16 {%0,%1,%2,%3}, [%4];" : "=r"(r[0]), "=r"(r[1]), "=r"(r[2]), "=r"(r[3]) : "r"(a) : "memory");
}
__device__ __forceinline__ void stm4(uint32_t a, uint32_t r0, uint32_t r1, uint32_t r2, uint32_t r3) {
  asm volatile("stmatrix.sync.aligned.m8n8.x4.shared.b16 [%0], {%1,%2,%3,%4};" :: "r"(a), "r"(r0), "r"(r1), "r"(r2), "r"(r3) : "memory");
}
__device__ __forceinline__ void mma16(float* d, uint32_t a0, uint32_t a1, uint32_t a2, uint32_t a3, uint32_t b0, uint32_t b1) {
  asm volatile("mma.sync.aligned.m16n8k16.row.col.f32.bf16.bf16.f32 {%0,%1,%2,%3}, {%4,%5,%6,%7}, {%8,%9}, {%0,%1,%2,%3};"
               : "+f"(d[0]), "+f"(d[1]), "+f"(d[2]), "+f"(d[3]) : "r"(a0), "r"(a1), "r"(a2), "r"(a3), "r"(b0), "r"(b1));
}
__device__ __forceinline__ void mma16z(float* d, uint32_t a0, uint32_t a1, uint32_t a2, uint32_t a3, uint32_t b0, uint32_t b1) {
  asm volatile("mma.sync.aligned.m16n8k16.row.col.f32.bf16.bf16.f32 {%0,%1,%2,%3}, {%4,%5,%6,%7}, {%8,%9}, {%10,%10,%10,%10};"
               : "=f"(d[0]), "=f"(d[1]), "=f"(d[2]), "=f"(d[3]) : "r"(a0), "r"(a1), "r"(a2), "r"(a3), "r"(b0), "r"(b1), "f"(0.f));
}
__device__ __forceinline__ void mma8(float* d, uint32_t a0, uint32_t a1, uint32_t b0) {
  asm volatile("mma.sync.aligned.m16n8k8.row.col.f32.bf16.bf16.f32 {%0,%1,%2,%3}, {%4,%5}, {%6}, {%0,%1,%2,%3};"
               : "+f"(d[0]), "+f"(d[1]), "+f"(d[2]), "+f"(d[3]) : "r"(a0), "r"(a1), "r"(b0));
}
__device__ __forceinline__ void mma8z(float* d, uint32_t a0, uint32_t a1, uint32_t b0) {
  asm volatile("mma.sync.aligned.m16n8k8.row.col.f32.bf16.bf16.f32 {%0,%1,%2,%3}, {%4,%5}, {%6}, {%7,%7,%7,%7};"
               : "=f"(d[0]), "=f"(d[1]), "=f"(d[2]), "=f"(d[3]) : "r"(a0), "r"(a1), "r"(b0), "f"(0.f));
}
__device__ __forceinline__ uint32_t pack_bf16(float lo, float hi) { uint32_t r; asm("cvt.rn.bf16x2.f32 %0, %1, %2;" : "=r"(r) : "f"(hi), "f"(lo)); return r; }
__device__ __forceinline__ uint32_t pack_f16(float lo, float hi) { uint32_t r; asm("cvt.rn.f16x2.f32 %0, %1, %2;" : "=r"(r) : "f"(hi), "f"(lo)); return r; }
__device__ __forceinline__ float2 unpack_f16(uint32_t v) { return __half22float2(*reinterpret_cast<__half2*>(&v)); }
__device__ __forceinline__ uint32_t absmax2(uint32_t a, uint32_t b) { uint32_t r; asm("max.xorsign.abs.bf16x2 %0, %1, %2;" : "=r"(r) : "r"(a), "r"(b)); return r; }
__device__ __forceinline__ uint32_t fold_absmax(uint32_t m) { m &= 0x7FFF7FFFu; return max(m & 0xFFFFu, m >> 16); }
__device__ __forceinline__ float ex2(float x) { float r; asm("ex2.approx.ftz.f32 %0, %1;" : "=f"(r) : "f"(x)); return r; }
__device__ __forceinline__ void sts32(uint32_t a, uint32_t v) { asm volatile("st.shared.u32 [%0], %1;" :: "r"(a), "r"(v) : "memory"); }
__device__ __forceinline__ void sts64f(uint32_t a, float x, float y) { asm volatile("st.shared.v2.f32 [%0], {%1,%2};" :: "r"(a), "f"(x), "f"(y) : "memory"); }
__device__ __forceinline__ float2 lds64f(uint32_t a) { float2 v; asm volatile("ld.shared.v2.f32 {%0,%1}, [%2];" : "=f"(v.x), "=f"(v.y) : "r"(a) : "memory"); return v; }
__device__ __forceinline__ uint32_t lds32(uint32_t a) { uint32_t v; asm volatile("ld.shared.u32 %0, [%1];" : "=r"(v) : "r"(a) : "memory"); return v; }
__device__ __forceinline__ uint4 lds128(uint32_t a) { uint4 v; asm volatile("ld.shared.v4.u32 {%0,%1,%2,%3}, [%4];" : "=r"(v.x), "=r"(v.y), "=r"(v.z), "=r"(v.w) : "r"(a) : "memory"); return v; }
__device__ __forceinline__ void st_async32(uint32_t a, uint32_t v, uint32_t mb) {
  asm volatile("st.async.weak.shared::cluster.mbarrier::complete_tx::bytes.b32 [%0], %1, [%2];" :: "r"(a), "r"(v), "r"(mb) : "memory");
}
__device__ __forceinline__ uint4 ldv128(const void* p) {
  uint4 v; asm volatile("ld.volatile.global.v4.u32 {%0,%1,%2,%3}, [%4];" : "=r"(v.x), "=r"(v.y), "=r"(v.z), "=r"(v.w) : "l"(p) : "memory"); return v;
}
__device__ __forceinline__ uint32_t ldv32(const void* p) { uint32_t v; asm volatile("ld.volatile.global.u32 %0, [%1];" : "=r"(v) : "l"(p) : "memory"); return v; }
__device__ __forceinline__ float bf_lo(uint32_t v) { return __uint_as_float(v << 16); }
__device__ __forceinline__ float bf_hi(uint32_t v) { return __uint_as_float(v & 0xFFFF0000u); }

__device__ __forceinline__ void wgmma_rs192(float* d, uint32_t a0, uint32_t a1, uint32_t a2, uint32_t a3, uint64_t desc, int acc) {
  asm volatile("{ .reg .pred p; setp.ne.b32 p, %101, 0;\n"
    "wgmma.mma_async.sync.aligned.m64n192k16.f32.bf16.bf16 {%0,%1,%2,%3,%4,%5,%6,%7,%8,%9,%10,%11,%12,%13,%14,%15,%16,%17,%18,%19,%20,%21,%22,%23,%24,%25,%26,%27,%28,%29,%30,%31,%32,%33,%34,%35,%36,%37,%38,%39,%40,%41,%42,%43,%44,%45,%46,%47,%48,%49,%50,%51,%52,%53,%54,%55,%56,%57,%58,%59,%60,%61,%62,%63,%64,%65,%66,%67,%68,%69,%70,%71,%72,%73,%74,%75,%76,%77,%78,%79,%80,%81,%82,%83,%84,%85,%86,%87,%88,%89,%90,%91,%92,%93,%94,%95}, {%96,%97,%98,%99}, %100, p, 1, 1, 1; }"
    :
      "+f"(d[0]), "+f"(d[1]), "+f"(d[2]), "+f"(d[3]), "+f"(d[4]), "+f"(d[5]), "+f"(d[6]), "+f"(d[7]), "+f"(d[8]), "+f"(d[9]), "+f"(d[10]), "+f"(d[11]),
      "+f"(d[12]), "+f"(d[13]), "+f"(d[14]), "+f"(d[15]), "+f"(d[16]), "+f"(d[17]), "+f"(d[18]), "+f"(d[19]), "+f"(d[20]), "+f"(d[21]), "+f"(d[22]), "+f"(d[23]),
      "+f"(d[24]), "+f"(d[25]), "+f"(d[26]), "+f"(d[27]), "+f"(d[28]), "+f"(d[29]), "+f"(d[30]), "+f"(d[31]), "+f"(d[32]), "+f"(d[33]), "+f"(d[34]), "+f"(d[35]),
      "+f"(d[36]), "+f"(d[37]), "+f"(d[38]), "+f"(d[39]), "+f"(d[40]), "+f"(d[41]), "+f"(d[42]), "+f"(d[43]), "+f"(d[44]), "+f"(d[45]), "+f"(d[46]), "+f"(d[47]),
      "+f"(d[48]), "+f"(d[49]), "+f"(d[50]), "+f"(d[51]), "+f"(d[52]), "+f"(d[53]), "+f"(d[54]), "+f"(d[55]), "+f"(d[56]), "+f"(d[57]), "+f"(d[58]), "+f"(d[59]),
      "+f"(d[60]), "+f"(d[61]), "+f"(d[62]), "+f"(d[63]), "+f"(d[64]), "+f"(d[65]), "+f"(d[66]), "+f"(d[67]), "+f"(d[68]), "+f"(d[69]), "+f"(d[70]), "+f"(d[71]),
      "+f"(d[72]), "+f"(d[73]), "+f"(d[74]), "+f"(d[75]), "+f"(d[76]), "+f"(d[77]), "+f"(d[78]), "+f"(d[79]), "+f"(d[80]), "+f"(d[81]), "+f"(d[82]), "+f"(d[83]),
      "+f"(d[84]), "+f"(d[85]), "+f"(d[86]), "+f"(d[87]), "+f"(d[88]), "+f"(d[89]), "+f"(d[90]), "+f"(d[91]), "+f"(d[92]), "+f"(d[93]), "+f"(d[94]), "+f"(d[95])
    : "r"(a0), "r"(a1), "r"(a2), "r"(a3), "l"(desc), "r"(acc));
}

__device__ __forceinline__ void wgmma_rs256(float* d, uint32_t a0, uint32_t a1, uint32_t a2, uint32_t a3, uint64_t desc, int acc) {
  asm volatile("{ .reg .pred p; setp.ne.b32 p, %133, 0;\n"
    "wgmma.mma_async.sync.aligned.m64n256k16.f32.bf16.bf16 {%0,%1,%2,%3,%4,%5,%6,%7,%8,%9,%10,%11,%12,%13,%14,%15,%16,%17,%18,%19,%20,%21,%22,%23,%24,%25,%26,%27,%28,%29,%30,%31,%32,%33,%34,%35,%36,%37,%38,%39,%40,%41,%42,%43,%44,%45,%46,%47,%48,%49,%50,%51,%52,%53,%54,%55,%56,%57,%58,%59,%60,%61,%62,%63,%64,%65,%66,%67,%68,%69,%70,%71,%72,%73,%74,%75,%76,%77,%78,%79,%80,%81,%82,%83,%84,%85,%86,%87,%88,%89,%90,%91,%92,%93,%94,%95,%96,%97,%98,%99,%100,%101,%102,%103,%104,%105,%106,%107,%108,%109,%110,%111,%112,%113,%114,%115,%116,%117,%118,%119,%120,%121,%122,%123,%124,%125,%126,%127}, {%128,%129,%130,%131}, %132, p, 1, 1, 1; }"
    :
      "+f"(d[0]), "+f"(d[1]), "+f"(d[2]), "+f"(d[3]), "+f"(d[4]), "+f"(d[5]), "+f"(d[6]), "+f"(d[7]), "+f"(d[8]), "+f"(d[9]), "+f"(d[10]), "+f"(d[11]),
      "+f"(d[12]), "+f"(d[13]), "+f"(d[14]), "+f"(d[15]), "+f"(d[16]), "+f"(d[17]), "+f"(d[18]), "+f"(d[19]), "+f"(d[20]), "+f"(d[21]), "+f"(d[22]), "+f"(d[23]),
      "+f"(d[24]), "+f"(d[25]), "+f"(d[26]), "+f"(d[27]), "+f"(d[28]), "+f"(d[29]), "+f"(d[30]), "+f"(d[31]), "+f"(d[32]), "+f"(d[33]), "+f"(d[34]), "+f"(d[35]),
      "+f"(d[36]), "+f"(d[37]), "+f"(d[38]), "+f"(d[39]), "+f"(d[40]), "+f"(d[41]), "+f"(d[42]), "+f"(d[43]), "+f"(d[44]), "+f"(d[45]), "+f"(d[46]), "+f"(d[47]),
      "+f"(d[48]), "+f"(d[49]), "+f"(d[50]), "+f"(d[51]), "+f"(d[52]), "+f"(d[53]), "+f"(d[54]), "+f"(d[55]), "+f"(d[56]), "+f"(d[57]), "+f"(d[58]), "+f"(d[59]),
      "+f"(d[60]), "+f"(d[61]), "+f"(d[62]), "+f"(d[63]), "+f"(d[64]), "+f"(d[65]), "+f"(d[66]), "+f"(d[67]), "+f"(d[68]), "+f"(d[69]), "+f"(d[70]), "+f"(d[71]),
      "+f"(d[72]), "+f"(d[73]), "+f"(d[74]), "+f"(d[75]), "+f"(d[76]), "+f"(d[77]), "+f"(d[78]), "+f"(d[79]), "+f"(d[80]), "+f"(d[81]), "+f"(d[82]), "+f"(d[83]),
      "+f"(d[84]), "+f"(d[85]), "+f"(d[86]), "+f"(d[87]), "+f"(d[88]), "+f"(d[89]), "+f"(d[90]), "+f"(d[91]), "+f"(d[92]), "+f"(d[93]), "+f"(d[94]), "+f"(d[95]),
      "+f"(d[96]), "+f"(d[97]), "+f"(d[98]), "+f"(d[99]), "+f"(d[100]), "+f"(d[101]), "+f"(d[102]), "+f"(d[103]), "+f"(d[104]), "+f"(d[105]), "+f"(d[106]), "+f"(d[107]),
      "+f"(d[108]), "+f"(d[109]), "+f"(d[110]), "+f"(d[111]), "+f"(d[112]), "+f"(d[113]), "+f"(d[114]), "+f"(d[115]), "+f"(d[116]), "+f"(d[117]), "+f"(d[118]), "+f"(d[119]),
      "+f"(d[120]), "+f"(d[121]), "+f"(d[122]), "+f"(d[123]), "+f"(d[124]), "+f"(d[125]), "+f"(d[126]), "+f"(d[127])
    : "r"(a0), "r"(a1), "r"(a2), "r"(a3), "l"(desc), "r"(acc));
}

__device__ __forceinline__ void wg_fence() { asm volatile("wgmma.fence.sync.aligned;" ::: "memory"); }
__device__ __forceinline__ void wg_commit() { asm volatile("wgmma.commit_group.sync.aligned;" ::: "memory"); }
template <int N> __device__ __forceinline__ void wg_wait() { asm volatile("wgmma.wait_group.sync.aligned %0;" :: "n"(N) : "memory"); }
__device__ __forceinline__ void tma5d(uint32_t dst, const CUtensorMap* tm, int c0, int c4, uint32_t mb) {
  asm volatile("cp.async.bulk.tensor.5d.shared::cluster.global.mbarrier::complete_tx::bytes [%0], [%1, {%3, %5, %5, %5, %4}], [%2];"
               :: "r"(dst), "l"((uint64_t)tm), "r"(mb), "r"(c0), "r"(c4), "r"(0) : "memory");
}
__device__ __forceinline__ void tma5d_mc(uint32_t dst, const CUtensorMap* tm, int c0, int c4, uint32_t mb) {
  asm volatile("cp.async.bulk.tensor.5d.shared::cluster.global.mbarrier::complete_tx::bytes.multicast::cluster [%0], [%1, {%3, %5, %5, %5, %4}], [%2], %6;"
               :: "r"(dst), "l"((uint64_t)tm), "r"(mb), "r"(c0), "r"(c4), "r"(0), "h"((unsigned short)3) : "memory");
}
__device__ __forceinline__ void mbar_arrive_cluster(uint32_t a) { asm volatile("mbarrier.arrive.shared::cluster.b64 _, [%0];" :: "r"(a) : "memory"); }
__device__ __forceinline__ void ldg128(uint32_t* r, const uint8_t* p) {
  asm volatile("ld.global.L1::no_allocate.v4.u32 {%0,%1,%2,%3}, [%4];" : "=r"(r[0]), "=r"(r[1]), "=r"(r[2]), "=r"(r[3]) : "l"(p) : "memory");
}
__device__ __forceinline__ uint32_t ld_relaxed(const unsigned* p) { uint32_t v; asm volatile("ld.relaxed.gpu.global.u32 %0, [%1];" : "=r"(v) : "l"(p) : "memory"); return v; }
__device__ __forceinline__ uint32_t ld_acquire(const unsigned* p) { uint32_t v; asm volatile("ld.acquire.gpu.global.u32 %0, [%1];" : "=r"(v) : "l"(p) : "memory"); return v; }
__device__ __forceinline__ void red_release(unsigned* p) { asm volatile("red.release.gpu.global.add.u32 [%0], 1;" :: "l"(p) : "memory"); }
__device__ __forceinline__ void red_relaxed(unsigned* p) { asm volatile("red.relaxed.gpu.global.add.u32 [%0], 1;" :: "l"(p) : "memory"); }
__device__ __forceinline__ void fence_gpu() { asm volatile("fence.acq_rel.gpu;" ::: "memory"); }
__device__ __forceinline__ void wait_count(const unsigned* p, uint32_t target) {
  int it = 0;
  while (__any_sync(~0u, (int)(ld_acquire(p) - target) < 0)) { if (give_up(++it, 5)) break; __nanosleep(64); }
}

constexpr int G_ST = 32768, G_NST = 7, G_MB = G_ST * G_NST, GB_W = G_MB  , GB_FULL = G_MB + 32, GB_EMPTY = G_MB + 96, G_SMEM = G_MB + 160;

constexpr int C_WV = 0, C_WO = 65536, C_KVQ = 131072, KVQ_ST = 20480, C_VP = 192512, C_MEM = 196608, C_QM = 204800, QM_BUF = 6144,
              C_OT = 217088, C_SX = 219136, C_S2 = 220672, C_MISC = 222720;
constexpr int MB_WQ = C_MISC, MB_WK = C_MISC + 8, MB_WV = C_MISC + 16, MB_WO = C_MISC + 24, MB_PEER = C_MISC + 32  , MB_KVQ = C_MISC + 48  ;
constexpr int C_MX = C_MISC + 96;
constexpr int C_SC = C_MISC + 160;
constexpr int C_WM = C_MISC + 192;
constexpr int C_XE = C_MISC + 256;
constexpr int C_GT = C_MISC + 512;
constexpr int C_DBG = C_MISC + 768;
constexpr int C_SMEM = C_DBG;
#define STAMP(slot)
#define STAMP2(slot)
#define STAMP_NEXT

__device__ __forceinline__ int fresh(int v) { asm volatile("" : "+r"(v)); return v; }

struct Args {
  CUtensorMap tmq, tmk, tmv, tmo;
  CUtensorMap pw[3];
  CUtensorMap pb[4];
  const bf16* x; const bf16* mem0; const bf16* wo; const bf16* gate_w; bf16* out;
  uint32_t zero;
  uint16_t first[NGC + 2];
  uint32_t job[MAXJOBS];
};
constexpr int K_SMEM = C_SMEM > G_SMEM ? C_SMEM : G_SMEM;

__device__ __forceinline__ void load_a(uint32_t* a, const uint8_t* p0, const uint8_t* p1) {
  ldg128(a, p0); ldg128(a + 4, p1); ldg128(a + 8, p0 + 64); ldg128(a + 12, p1 + 64);
}
__device__ __forceinline__ void frag_a(uint32_t* u, const uint32_t* a, uint32_t z) {
#pragma unroll
  for (int i = 0; i < 16; i++) { u[i] = a[(i & 8) | ((i & 1) << 2) | (i & 2) | ((i >> 2) & 1)] ^ z; asm volatile("" : "+r"(u[i])); }
}
#define GSTAMP(i)

__global__ void __launch_bounds__(384, 1)
fused_kernel(const __grid_constant__ Args args) {
  extern __shared__ __align__(1024) uint8_t smem[];
  const int tid = threadIdx.x;
  int lane = tid & 31;
  asm volatile("" : "+r"(lane));
  const int warp = __shfl_sync(~0u, tid >> 5, 0);
  const int cta = blockIdx.x, h = (cta >> 1) & 31, j = cta & 1;
  const uint32_t sb = smem_u32(smem);

  if (tid == 0 && cta >= 64) {
    for (int i = 0; i < 4; i++) mbar_init(sb + GB_W + 8 * i, 1);
    for (int i = 0; i < G_NST; i++) { mbar_init(sb + GB_FULL + 8 * i, 1); mbar_init(sb + GB_EMPTY + 8 * i, 16); }
    asm volatile("fence.mbarrier_init.release.cluster;" ::: "memory");
    if (cta < 128)
      for (int i = 0; i < 4; i++) {
        mbar_expect_tx(sb + GB_W + 8 * i, 49152);
        for (int b = 0; b < 3; b++) tma5d(sb + b * 65536 + i * 16384, &args.pw[b], h * DH + j * 64, 4 * i, sb + GB_W + 8 * i);
      }
  }
  if (tid == 0 && cta < 64) {
    mbar_init(sb + MB_WQ, 1); mbar_init(sb + MB_WK, 1); mbar_init(sb + MB_WV, 1); mbar_init(sb + MB_WO, 1);
    mbar_init(sb + MB_PEER, 1); mbar_init(sb + MB_PEER + 8, 1);
    for (int i = 0; i < 3; i++) mbar_init(sb + MB_KVQ + 8 * i, 1);
    asm volatile("fence.mbarrier_init.release.cluster;" ::: "memory");
    const int col = h * DH + j * 64;
    mbar_expect_tx(sb + MB_WQ, 65536); tma2d(sb + C_WO, &args.tmq, col, 0, sb + MB_WQ); tma2d(sb + C_WO + 32768, &args.tmq, col, 256, sb + MB_WQ);
    mbar_expect_tx(sb + MB_WK, 65536); tma2d(sb + C_KVQ, &args.tmk, col, 0, sb + MB_WK); tma2d(sb + C_KVQ + 32768, &args.tmk, col, 256, sb + MB_WK);
    mbar_expect_tx(sb + MB_WV, 65536); tma2d(sb + C_WV, &args.tmv, col, 0, sb + MB_WV); tma2d(sb + C_WV + 32768, &args.tmv, col, 256, sb + MB_WV);
    mbar_expect_tx(sb + MB_PEER, 3072); mbar_expect_tx(sb + MB_PEER + 8, 3072);
  }
  const uint32_t tag = ldv32(&g_done) / NCTA + 1;
  asm volatile("barrier.cluster.arrive.aligned; barrier.cluster.wait.aligned;" ::: "memory");
  auto issue_stage = [&](int seg) {
    const int stg = seg % 3;
    const uint8_t* src = g_qkv + (size_t)(seg * NH + h) * BLK_BYTES;
    const uint32_t mb = sb + MB_KVQ + 8 * stg, dst = sb + C_KVQ + stg * KVQ_ST;
    mbar_expect_tx(mb, KVQ_ST + 64);
    bulk_g2s(dst, src, 16384, mb);
    bulk_g2s(dst + 16384, src + 16384 + j * 4096, 4096, mb);
    bulk_g2s(sb + C_GT + stg * 64, g_gate + seg * SEGL + 16 * j, 64, mb);
  };

  if (cta >= 64 && warp < 8) {
    asm volatile("setmaxnreg.inc.sync.aligned.u32 232;");
    const int wg = warp >> 2, w = warp & 3, g = lane >> 2, t = lane & 3;
    const uint64_t dsc_hi = (uint64_t)((2048 >> 4) | (1u << 30)) << 32;
    uint32_t A[4][16], U[2][16];
    GSTAMP(0);
    if (cta < 128) {
      float acc[96];
      const uint8_t* p0 = reinterpret_cast<const uint8_t*>(args.x) + (size_t)(wg * 64 + w * 16 + g) * (DM * 2) + t * 16;
#pragma unroll
      for (int i = 0; i < 4; i++) load_a(A[i], p0 + i * 128, p0 + i * 128 + 8192);
      const uint64_t dsc = dsc_hi | (uint64_t)(((sb >> 4) & 0x3FFF) | ((65536 >> 4) << 16));
      uint8_t* dst = g_qkv + (size_t)((2 * wg + (w >> 1)) * NH + h) * BLK_BYTES + (16 * (w & 1) + g) * 256;
      const uint32_t c0 = ((8 * j + t) ^ g) << 4;
      unsigned* fl = g_fq + (2 * wg + (w >> 1)) * NH + h;
      if (wg == 1) bar_sync<1, 256>();
      for (int it = 0; it < 16; it++) {
#pragma unroll
        for (int kc = 0; kc < 8; kc++) {
          if (it == 0) mbar_wait(sb + GB_W + 8 * (kc >> 1), 0);
          uint32_t* a = U[kc & 1];
          frag_a(a, A[kc & 3], args.zero);
          wg_fence();
          wgmma_rs192(acc, a[0], a[1], a[2], a[3], dsc + kc * 512, kc != 0);
          wgmma_rs192(acc, a[4], a[5], a[6], a[7], dsc + kc * 512 + 64, 1);
          wgmma_rs192(acc, a[8], a[9], a[10], a[11], dsc + kc * 512 + 256, 1);
          wgmma_rs192(acc, a[12], a[13], a[14], a[15], dsc + kc * 512 + 320, 1);
          wg_commit();
          const uint8_t* pn = p0 + (kc < 4 ? (kc + 4) * 128 : 128 * DM * 2 + (kc - 4) * 128);
          if (kc < 4 || it < 15) load_a(A[kc & 3], pn, pn + 8192);
          if (kc == 0 && it > 0) { __syncwarp(); if (lane == 0) red_release(fl - 4 * NH); }
          if (kc == 3 && it == 0 && wg == 0) bar_arrive<1, 256>();
          wg_wait<1>();
        }
        wg_wait<0>();
#pragma unroll
        for (int b = 0; b < 6; b++) {
          const float* d = acc + 16 * b;
          uint8_t* q = dst + (b >> 1) * 8192 + (c0 ^ ((b & 1) << 6));
          *reinterpret_cast<uint4*>(q) = make_uint4(pack_bf16(d[0], d[1]), pack_bf16(d[4], d[5]), pack_bf16(d[8], d[9]), pack_bf16(d[12], d[13]));
          *reinterpret_cast<uint4*>(q + 2048) = make_uint4(pack_bf16(d[2], d[3]), pack_bf16(d[6], d[7]), pack_bf16(d[10], d[11]), pack_bf16(d[14], d[15]));
        }
        p0 += 128 * DM * 2; dst += (size_t)4 * NH * BLK_BYTES; fl += 4 * NH;
      }
      __syncwarp();
      if (lane == 0) red_release(fl - 4 * NH);
    }
    GSTAMP(1);
    const uint32_t ea = mapa(sb + GB_EMPTY, lane & 1);
    if (lane < 2 * G_NST) mbar_arrive_cluster(ea + 8 * (lane >> 1));
    const int gc = (cta - 64) >> 1;
    const int jn = args.first[gc + 1];
    int ji = args.first[gc];
    const uint64_t dsc = dsc_hi | (uint64_t)(((sb >> 4) & 0x3FFF) | ((8192 >> 4) << 16));
    uint32_t st = 0, ph = 0;
    bool loaded = false, gate_ok = false;
    const uint8_t *p0, *p1;
    auto set_a = [&](uint32_t job) {
      const int row = ((job >> 1) & 7) * 256 + j * 128 + wg * 64 + w * 16 + g;
      const bool fin = job & 1;
      p0 = (fin ? reinterpret_cast<const uint8_t*>(g_a) + (size_t)row * (KA * 2) + ((job >> 8) & 127) * 128
                : reinterpret_cast<const uint8_t*>(args.x) + (size_t)row * (DM * 2)) + t * 16;
      p1 = p0 + (fin ? 8 * KA * 2 : 8 * DM * 2);
    };
    auto dep_ptr = [&](uint32_t job) { return (((job >> 8) & 127) < 64 ? g_fo : g_fh) + ((job >> 1) & 7) * 16 + j * 8 + warp; };
    auto dep_cnt = [&](uint32_t job) { return tag * (((job >> 8) & 127) < 64 ? 32u : 14u); };
    if (wg == 1) bar_sync<2, 256>();
    bool lead = wg == 0;
    float acc[128];
    for (; ji < jn; ji++) {
      const uint32_t job = args.job[ji];
      if (!loaded) {
        if (job & 1) wait_count(dep_ptr(job), dep_cnt(job));
        set_a(job);
        load_a(A[0], p0, p1); load_a(A[1], p0 + 128, p1 + 128);
      }
      const uint32_t nxt = args.job[ji + 1];
      const uint32_t dep = ld_relaxed(dep_ptr(nxt));
      const int nk = (job >> 15) & 127;
      uint32_t pst = 0;
      for (int k = 0; k < nk; k += 2) {
#pragma unroll
        for (int u = 0; u < 2; u++) {
          uint32_t* a = U[u];
          mbar_wait(sb + GB_FULL + 8 * st, ph);
          frag_a(a, A[u], args.zero);
          const uint64_t d = dsc + st * (G_ST >> 4);
          wg_fence();
          wgmma_rs256(acc, a[0], a[1], a[2], a[3], d, u != 0 || k != 0);
          wgmma_rs256(acc, a[4], a[5], a[6], a[7], d + 64, 1);
          wgmma_rs256(acc, a[8], a[9], a[10], a[11], d + 256, 1);
          wgmma_rs256(acc, a[12], a[13], a[14], a[15], d + 320, 1);
          wg_commit();
          if (k + 2 < nk) load_a(A[u], p0 + (u + 2) * 128, p1 + (u + 2) * 128);
          if (u == 0 && k == 2 && lead) { bar_arrive<2, 256>(); lead = false; }
          wg_wait<1>();
          if ((u != 0 || k != 0) && lane < 2) mbar_arrive_cluster(ea + 8 * pst);
          pst = st;
          if (++st == G_NST) { st = 0; ph ^= 1; }
        }
        p0 += 256; p1 += 256;
      }
      wg_wait<0>();
      if (lane < 2) mbar_arrive_cluster(ea + 8 * pst);
      loaded = ji + 1 < jn && (!(nxt & 1) || (int)(dep - dep_cnt(nxt)) >= 0);
      if (loaded) {
        if (nxt & 1) fence_gpu();
        set_a(nxt);
        load_a(A[0], p0, p1); load_a(A[1], p0 + 128, p1 + 128);
      }
      const int m16 = ((job >> 1) & 7) * 16 + j * 8 + warp, n = (job >> 4) & 15;
      const int row = m16 * 16 + g;
      if (!(job & 1)) {
        if (!gate_ok) {
          int it = 0;
          while (!__all_sync(~0u, ldv32(&g_pub[lane]) == tag && ldv32(&g_pub[lane + 32]) == tag)) { if (give_up(++it, 6)) break; }
          fence_gpu();
          gate_ok = true;
        }
        const float s0 = 1.0f - __ldcg(g_gate + row), s1 = 1.0f - __ldcg(g_gate + row + 8);
        bf16* q = g_a + (size_t)row * KA + HD + n * 128 + 8 * t;
#pragma unroll
        for (int b = 0; b < 4; b++) {
          uint32_t lo[4], hi[4];
#pragma unroll
          for (int i = 0; i < 4; i++) {
            const float* ga = acc + 16 * b + 4 * i;
            float v[4];
#pragma unroll
            for (int e = 0; e < 4; e++) v[e] = __fdividef(ga[64 + e] * (e < 2 ? s0 : s1), 1.0f + ex2(ga[e] * -1.4426950408889634f));
            lo[i] = pack_bf16(v[0], v[1]); hi[i] = pack_bf16(v[2], v[3]);
          }
          *reinterpret_cast<uint4*>(q + 32 * b) = make_uint4(lo[0], lo[1], lo[2], lo[3]);
          *reinterpret_cast<uint4*>(q + 32 * b + 8 * KA) = make_uint4(hi[0], hi[1], hi[2], hi[3]);
        }
        __syncwarp();
        if (lane == 0) red_release(g_fh + m16);
      } else {
        float* q = g_acc + (size_t)row * DM + n * 256 + 2 * t;
        unsigned* fc = g_fc + m16 * 2 + n;
        const uint32_t parts = job >> 23, base = (tag - 1) * parts;
        if (job & (1u << 22)) {
#pragma unroll
          for (int i = 0; i < 32; i++) {
            *reinterpret_cast<float2*>(q + 8 * i) = make_float2(acc[4 * i], acc[4 * i + 1]);
            *reinterpret_cast<float2*>(q + 8 * i + 8 * DM) = make_float2(acc[4 * i + 2], acc[4 * i + 3]);
          }
          __syncwarp();
          if (lane == 0) red_release(fc);
        } else {
          wait_count(fc, base + 1);
#pragma unroll
          for (int i = 0; i < 32; i++) {
            asm volatile("red.relaxed.gpu.global.add.v2.f32 [%0], {%1,%2};" :: "l"(q + 8 * i), "f"(acc[4 * i]), "f"(acc[4 * i + 1]) : "memory");
            asm volatile("red.relaxed.gpu.global.add.v2.f32 [%0], {%1,%2};" :: "l"(q + 8 * i + 8 * DM), "f"(acc[4 * i + 2]), "f"(acc[4 * i + 3]) : "memory");
          }
          __syncwarp();
          uint32_t tk = 0;
          if (lane == 0) asm volatile("atom.acq_rel.gpu.global.add.u32 %0, [%1], 1;" : "=r"(tk) : "l"(fc) : "memory");
          tk = __shfl_sync(~0u, tk, 0);
          if (tk == base + parts - 1) {
            const float4* s = reinterpret_cast<const float4*>(g_acc + (size_t)m16 * 16 * DM + n * 256) + 2 * lane;
            uint4* o = reinterpret_cast<uint4*>(args.out + (size_t)m16 * 16 * DM + n * 256) + lane;
#pragma unroll
            for (int r = 0; r < 32; r++) {
              const float4 v = __ldcg(s + (r >> 1) * (DM / 4) + (r & 1));
              acc[4 * r] = v.x; acc[4 * r + 1] = v.y; acc[4 * r + 2] = v.z; acc[4 * r + 3] = v.w;
            }
#pragma unroll
            for (int r = 0; r < 16; r++) {
              const float* a = acc + 8 * r;
              o[r * (DM / 8)] = make_uint4(pack_bf16(a[0], a[1]), pack_bf16(a[2], a[3]), pack_bf16(a[4], a[5]), pack_bf16(a[6], a[7]));
            }
          }
        }
      }
      GSTAMP(2 + ji - args.first[gc]);
    }
    if (lead) bar_arrive<2, 256>();
    asm volatile("barrier.cluster.arrive.aligned; barrier.cluster.wait.aligned;" ::: "memory");
  } else if (cta >= 64) {
    asm volatile("setmaxnreg.dec.sync.aligned.u32 40;");
    if (warp == 8 && lane == 0) {
      const int gc = (cta - 64) >> 1;
      const int jn = args.first[gc + 1];
      uint32_t st = 0, ph = 0;
      for (int ji = args.first[gc]; ji < jn; ji++) {
        const uint32_t job = args.job[ji];
        const int n = (job >> 4) & 15, k0 = (job >> 8) & 127, nk = (job >> 15) & 127;
        const CUtensorMap* tm = &args.pb[(job & 1) ? (k0 < 64 ? 2 : 3) : j];
        const int col = (job & 1) ? n * 256 + j * 128 : n * 128;
        for (int k = 0; k < nk; k++) {
          mbar_wait_cluster(sb + GB_EMPTY + 8 * st, ph);
          const uint32_t mb = sb + GB_FULL + 8 * st, dst = sb + st * G_ST + j * 16384;
          mbar_expect_tx(mb, G_ST);
          tma5d_mc(dst, tm, col, 2 * ((k0 & 63) + k), mb);
          tma5d_mc(dst + 8192, tm, col + 64, 2 * ((k0 & 63) + k), mb);
          if (++st == G_NST) { st = 0; ph ^= 1; }
        }
      }
      atomicAdd(&g_done, 1u);
    }
    __syncwarp();
    asm volatile("barrier.cluster.arrive.aligned; barrier.cluster.wait.aligned;" ::: "memory");
  } else if (warp < 8) {
    asm volatile("setmaxnreg.inc.sync.aligned.u32 " FAT_REGS ";");
    const int gam = warp >> 2, w = warp & 3;
    uint32_t wa[32][4], R[16][4];
    auto wv_off = [&](int l) { return (uint32_t)(((l & 7) + ((l >> 4) << 3)) * 128 + (((2 * w + ((l >> 3) & 1)) ^ (l & 7)) << 4)); };
    {
      mbar_wait(sb + (gam ? MB_WK : MB_WQ), 0);
      const uint32_t src = sb + (gam ? C_KVQ : C_WO) + wv_off(lane);
#pragma unroll
      for (int i = 0; i < 32; i++) ldm4t(wa[i], src + (((i + 16 * gam) & 31) << 11));
    }
    bar_sync<10, 384>();
    mbar_wait(sb + MB_WV, 0);
    {
      const uint32_t wv_a = sb + C_WV + gam * 32768 + wv_off(lane);
      uint32_t m = 0;
#pragma unroll
      for (int i = 0; i < 16; i++) {
        ldm4t(R[i], wv_a + (i << 11));
        m = absmax2(absmax2(m, absmax2(R[i][0], R[i][1])), absmax2(R[i][2], R[i][3]));
      }
      m = __reduce_max_sync(~0u, fold_absmax(m));
      if (lane == 0) sts32(sb + C_WM + warp * 4, m);
      bar_arrive<11, 384>();
    }
    const uint32_t peer_d = mapa(sb, j ^ 1) - sb;
    uint8_t* const ring_w = g_ring + warp * 1280;
    const int delay = POLL_DELAY;

    uint32_t pk[8];
    {
      const unsigned short* m0 = reinterpret_cast<const unsigned short*>(args.mem0);
#pragma unroll
      for (int i = 0; i < 8; i++) {
        const int d = (i >> 2) * 256 + warp * 32 + (i & 3) * 8 + (lane >> 2);
        pk[i] = (uint32_t)m0[(2 * (lane & 3)) * DM + d] | ((uint32_t)m0[(2 * (lane & 3) + 1) * DM + d] << 16);
      }
    }
    mbar_wait(sb + MB_WO, 0);
    uint32_t l16 = sb + lane * 16;
    for (int s = 0;; s++) {
      STAMP(0);
      stm4(l16 + C_MEM + warp * 512, pk[0], pk[1], pk[2], pk[3]);
      stm4(l16 + C_MEM + warp * 512 + 4096, pk[4], pk[5], pk[6], pk[7]);
      const uint32_t mem_ld0 = l16 + C_MEM + gam * 4096, mem_ld1 = l16 + C_MEM + (gam ^ 1) * 4096;
      bar_sync<1, 256>();
      STAMP2(1);
      float c0[4], c1[4], v0[4], v1[4];
      uint32_t b[16][4], Wo[16][4];
      ldm4t(b[0], mem_ld0);
      ldm4t(b[1], mem_ld0 + 512);
      mma16z(v0, R[0][0], R[0][1], R[0][2], R[0][3], b[0][0], b[0][1]);
      mma16z(c0, wa[0][0], wa[0][1], wa[0][2], wa[0][3], b[0][0], b[0][1]);
      mma16z(v1, R[1][0], R[1][1], R[1][2], R[1][3], b[0][2], b[0][3]);
      mma16z(c1, wa[1][0], wa[1][1], wa[1][2], wa[1][3], b[0][2], b[0][3]);
      {
        uint32_t m = b[0][0];
#pragma unroll
        for (int i = 0; i < 8; i++) m = absmax2(m, pk[i]);
        sts32(sb + C_MX + warp * 4, __reduce_max_sync(~0u, fold_absmax(m)));
      }
#pragma unroll
      for (int i = 1; i < 8; i++) {
        ldm4t(b[i + 1], i + 1 < 8 ? mem_ld0 + (i + 1) * 512 : mem_ld1);
        mma16(v0, R[2 * i][0], R[2 * i][1], R[2 * i][2], R[2 * i][3], b[i][0], b[i][1]);
        mma16(c0, wa[2 * i][0], wa[2 * i][1], wa[2 * i][2], wa[2 * i][3], b[i][0], b[i][1]);
        if (i >= 2) ldm4t(b[i + 7], mem_ld1 + (i - 1) * 512);
        mma16(v1, R[2 * i + 1][0], R[2 * i + 1][1], R[2 * i + 1][2], R[2 * i + 1][3], b[i][2], b[i][3]);
        mma16(c1, wa[2 * i + 1][0], wa[2 * i + 1][1], wa[2 * i + 1][2], wa[2 * i + 1][3], b[i][2], b[i][3]);
      }
      ldm4t(b[15], mem_ld1 + 7 * 512);
      const int la = fresh(lane);
      const uint32_t qb = sb + C_QM + (s & 1) * QM_BUF + (32 * (2 * j + (w >> 1)) + (la & 24) + ((4 * (w & 1)) ^ ((la >> 2) & 6)) + ((la >> 2) & 1)) * 16 + (la & 3) * 4;
      const uint32_t pm = sb + MB_PEER + (s & 1) * 8 + peer_d;
      const uint32_t wo_a = sb + C_WO + (warp >> 1) * 16384 + ((la & 7) + ((la >> 4) << 3)) * 128 + ((((warp & 1) * 4 + ((la >> 3) & 1)) ^ (la & 7)) << 4);
      const uint32_t vp = l16 + C_VP + w * 1024;
#pragma unroll
      for (int i = 8; i < 16; i++) {
        mma16(c0, wa[2 * i][0], wa[2 * i][1], wa[2 * i][2], wa[2 * i][3], b[i][0], b[i][1]);
        mma16(c1, wa[2 * i + 1][0], wa[2 * i + 1][1], wa[2 * i + 1][2], wa[2 * i + 1][3], b[i][2], b[i][3]);
        if (i == 9) sts64f(vp + gam * 512, gam ? v0[0] + v1[0] : v0[2] + v1[2], gam ? v0[1] + v1[1] : v0[3] + v1[3]);
        if (i == 11) {
          bar_sync_id(2 + w, 64);
          const float2 o = lds64f(vp + (gam ^ 1) * 512);
          const uint32_t v = pack_bf16((gam ? v0[2] + v1[2] : v0[0] + v1[0]) + o.x, (gam ? v0[3] + v1[3] : v0[1] + v1[1]) + o.y);
          const uint32_t a = (qb ^ (gam << 5)) + 4096;
          st_async32(a + peer_d, v, pm);
          sts32(a, v);
#pragma unroll
          for (int u = 0; u < WO_IN; u++) ldm4t(Wo[u], (wo_a ^ ((u & 1) << 5)) + ((u >> 1) << 11));
        }
      }
      {
        const uint32_t lo = pack_bf16(c0[0] + c1[0], c0[1] + c1[1]), hi = pack_bf16(c0[2] + c1[2], c0[3] + c1[3]);
        const uint32_t a = qb + gam * 2048;
        st_async32(a + peer_d, lo, pm);
        st_async32((a ^ 32) + peer_d, hi, pm);
        sts32(a, lo);
        sts32(a ^ 32, hi);
      }
      STAMP(2);
      if (s == NSEG - 1) { bar_arrive<6, 384>(); break; }
      bar_arrive<6, 384>();
#pragma unroll
      for (int u = WO_IN; u < WO_EARLY; u++) ldm4t(Wo[u], (wo_a ^ ((u & 1) << 5)) + ((u >> 1) << 11));
      if (warp == 7 && s + 2 < NSEG) {
        wait_count(g_fq + (s + 2) * NH + h, tag * 4);
        asm volatile("fence.proxy.async.global;" ::: "memory");
      }
      uint8_t* const rp = ring_w + (s & 7) * RING_SLOT;
      uint8_t* rp16 = rp + (la >> 3) * 256 + (la & 7) * 16;
      uint8_t* rp4 = rp + 1024 + la * 4;
      uint32_t ot_ld = sb + C_OT + (la ^ (((la >> 3) & 3) << 1)) * 16;
      asm volatile("" : "+l"(rp16), "+l"(rp4), "+r"(ot_ld));
      bar_sync<7, 384>();
      STAMP2(3);
#pragma unroll
      for (int i = 0; i < 4; i++) ldm4t(b[i], ot_ld + i * 512);
#pragma unroll
      for (int u = WO_EARLY; u < 16; u++) ldm4t(Wo[u], (wo_a ^ ((u & 1) << 5)) + ((u >> 1) << 11));
      mma16z(c0, Wo[0][0], Wo[0][1], Wo[0][2], Wo[0][3], b[0][0], b[0][1]);
      mma16z(c1, Wo[1][0], Wo[1][1], Wo[1][2], Wo[1][3], b[0][0], b[0][1]);
      mma16z(v0, Wo[2][0], Wo[2][1], Wo[2][2], Wo[2][3], b[0][2], b[0][3]);
      mma16z(v1, Wo[3][0], Wo[3][1], Wo[3][2], Wo[3][3], b[0][2], b[0][3]);
#pragma unroll
      for (int k = 1; k < 4; k++) {
        mma16(c0, Wo[4 * k][0], Wo[4 * k][1], Wo[4 * k][2], Wo[4 * k][3], b[k][0], b[k][1]);
        mma16(c1, Wo[4 * k + 1][0], Wo[4 * k + 1][1], Wo[4 * k + 1][2], Wo[4 * k + 1][3], b[k][0], b[k][1]);
        mma16(v0, Wo[4 * k + 2][0], Wo[4 * k + 2][1], Wo[4 * k + 2][2], Wo[4 * k + 2][3], b[k][2], b[k][3]);
        mma16(v1, Wo[4 * k + 3][0], Wo[4 * k + 3][1], Wo[4 * k + 3][2], Wo[4 * k + 3][3], b[k][2], b[k][3]);
      }
      asm volatile("red.relaxed.gpu.global.add.noftz.v4.f16x2 [%0], {%1,%2,%3,%4};"
                   :: "l"(rp16 + j * 10240), "r"(pack_f16(c0[0] + v0[0], c0[1] + v0[1])), "r"(pack_f16(c0[2] + v0[2], c0[3] + v0[3])),
                      "r"(pack_f16(c1[0] + v1[0], c1[1] + v1[1])), "r"(pack_f16(c1[2] + v1[2], 1.0f)) : "memory");
      asm volatile("red.relaxed.gpu.global.add.noftz.f16x2 [%0], %1;" :: "l"(rp4 + j * 10240), "r"(pack_f16(c1[3] + v1[3], 1.0f)) : "memory");
      bar_arrive<9, 384>();
      STAMP(4);
      if (warp == 7 && s + 2 < NSEG && la == 0) issue_stage(s + 2);
      const uint32_t wv_a = sb + C_WV + gam * 32768 + wv_off(fresh(lane));
      const float sc = __uint_as_float(lds32(sb + C_SC));
#pragma unroll
      for (int i = 0; i < WV_A; i++) ldm4t(R[i], wv_a + (i << 11));
      {
        float z = __uint_as_float(R[WV_A - 1][3] & 1u);
        for (int i = 0; i < delay; i++) asm volatile("fma.rn.f32 %0, %0, %0, %0; fma.rn.f32 %0, %0, %0, %0; fma.rn.f32 %0, %0, %0, %0; fma.rn.f32 %0, %0, %0, %0;" : "+f"(z));
        rp16 += __float_as_uint(z) >> 8;
      }
      STAMP(5);
      uint4 a0 = ldv128(rp16), a1 = ldv128(rp16 + 10240);
      uint32_t b0 = ldv32(rp4), b1 = ldv32(rp4 + 10240);
#pragma unroll
      for (int i = WV_A; i < 16; i++) ldm4t(R[i], wv_a + (i << 11));
      int it = 0;
      while (!__all_sync(~0u, ((a0.w & a1.w & b0 & b1) >> 16) == 0x5000u)) {
        if (give_up(++it, 3)) break;
        a0 = ldv128(rp16); a1 = ldv128(rp16 + 10240); b0 = ldv32(rp4); b1 = ldv32(rp4 + 10240);
      }
      a0.w = __byte_perm(a0.w, b0, 0x5410); a1.w = __byte_perm(a1.w, b1, 0x5410);
      float2 f;
      f = unpack_f16(a0.x); pk[0] = pack_bf16(f.x * sc, f.y * sc);
      f = unpack_f16(a0.y); pk[1] = pack_bf16(f.x * sc, f.y * sc);
      f = unpack_f16(a0.z); pk[2] = pack_bf16(f.x * sc, f.y * sc);
      f = unpack_f16(a0.w); pk[3] = pack_bf16(f.x * sc, f.y * sc);
      f = unpack_f16(a1.x); pk[4] = pack_bf16(f.x * sc, f.y * sc);
      f = unpack_f16(a1.y); pk[5] = pack_bf16(f.x * sc, f.y * sc);
      f = unpack_f16(a1.z); pk[6] = pack_bf16(f.x * sc, f.y * sc);
      f = unpack_f16(a1.w); pk[7] = pack_bf16(f.x * sc, f.y * sc);
      STAMP_NEXT;
    }
  } else {
    asm volatile("setmaxnreg.dec.sync.aligned.u32 " AUX_REGS ";");
    const int w = warp - 8, at = tid - 256;
    {
      if (at < 80) {
        const int u = cta * 10 + at % 10;
        *reinterpret_cast<uint4*>(g_ring + (at / 10) * RING_SLOT + (u >> 3) * 256 + (u & 7) * 16) = make_uint4(0, 0, 0, 0);
      }
      uint32_t mx = 0, mo = 0;
      const uint4 gw0 = __ldg(reinterpret_cast<const uint4*>(args.gate_w) + lane), gw1 = __ldg(reinterpret_cast<const uint4*>(args.gate_w) + 32 + lane);
#pragma unroll 2
      for (int r = 0; r < 8; r++) {
        const int tok = cta * SEGL + w * 8 + r;
        const uint4* xr = reinterpret_cast<const uint4*>(args.x + (size_t)tok * DM);
        const uint4 a = __ldg(xr + lane), b = __ldg(xr + 32 + lane);
        float acc = bf_lo(a.x) * bf_lo(gw0.x) + bf_hi(a.x) * bf_hi(gw0.x) + bf_lo(a.y) * bf_lo(gw0.y) + bf_hi(a.y) * bf_hi(gw0.y) +
                    bf_lo(a.z) * bf_lo(gw0.z) + bf_hi(a.z) * bf_hi(gw0.z) + bf_lo(a.w) * bf_lo(gw0.w) + bf_hi(a.w) * bf_hi(gw0.w) +
                    bf_lo(b.x) * bf_lo(gw1.x) + bf_hi(b.x) * bf_hi(gw1.x) + bf_lo(b.y) * bf_lo(gw1.y) + bf_hi(b.y) * bf_hi(gw1.y) +
                    bf_lo(b.z) * bf_lo(gw1.z) + bf_hi(b.z) * bf_hi(gw1.z) + bf_lo(b.w) * bf_lo(gw1.w) + bf_hi(b.w) * bf_hi(gw1.w);
        mx = absmax2(absmax2(mx, absmax2(absmax2(a.x, a.y), absmax2(a.z, a.w))), absmax2(absmax2(b.x, b.y), absmax2(b.z, b.w)));
#pragma unroll
        for (int o = 16; o; o >>= 1) acc += __shfl_xor_sync(~0u, acc, o);
        if (lane == 0) g_gate[tok] = __fdividef(1.0f, 1.0f + __expf(-acc));
      }
      const uint4* wr = reinterpret_cast<const uint4*>(args.wo + (size_t)(h * DH + w * 32) * DM + j * 256) + lane;
#pragma unroll 8
      for (int r = 0; r < 32; r++) {
        const uint4 a = __ldg(wr + r * (DM / 8));
        mo = absmax2(mo, absmax2(absmax2(a.x, a.y), absmax2(a.z, a.w)));
      }
      mx = __reduce_max_sync(~0u, fold_absmax(mx));
      mo = __reduce_max_sync(~0u, fold_absmax(mo));
      if (lane == 0) { sts32(sb + C_WM + 32 + w * 4, mx); sts32(sb + C_WM + 48 + w * 4, mo); }
      __threadfence();
    }
    bar_sync<10, 384>();
    if (at == 0) {
      mbar_expect_tx(sb + MB_WO, 65536);
      for (int i = 0; i < 4; i++) tma2d(sb + C_WO + i * 16384, &args.tmo, j * 256 + i * 64, h * DH, sb + MB_WO);
    }
    bar_sync<11, 384>();
    int wexp;
    {
      if (at == 0) {
        const uint4 a = lds128(sb + C_WM), b = lds128(sb + C_WM + 16), c = lds128(sb + C_WM + 32), d = lds128(sb + C_WM + 48);
        uint4 r;
        r.x = tag;
        r.y = max(max(c.x, c.y), max(c.z, c.w)) >> 7;
        r.z = max(max(max(a.x, a.y), max(a.z, a.w)), max(max(b.x, b.y), max(b.z, b.w))) >> 7;
        r.w = max(max(d.x, d.y), max(d.z, d.w)) >> 7;
        asm volatile("st.volatile.global.v4.u32 [%0], {%1,%2,%3,%4};" :: "l"(&g_pub[cta]), "r"(r.x), "r"(r.y), "r"(r.z), "r"(r.w) : "memory");
      }
      uint4 r0, r1;
      int it = 0;
      while (true) {
        r0 = ldv128(&g_pub[lane]); r1 = ldv128(&g_pub[lane + 32]);
        if (__all_sync(~0u, r0.x == tag && r1.x == tag)) break;
        if (give_up(++it, 4)) break;
      }
      __threadfence();
      if (w == 0) { sts32(sb + C_XE + lane * 4, r0.y); sts32(sb + C_XE + 128 + lane * 4, r1.y); }
      wexp = (int)__reduce_max_sync(~0u, max(r0.z, r1.z)) + (int)__reduce_max_sync(~0u, max(r0.w, r1.w)) - 3 * 126 + 21 - 14;
      bar_sync<8, 128>();
    }
    if (w == 0) {
      for (int i = 0; i < 2; i++) {
        wait_count(g_fq + i * NH + h, tag * 4);
        asm volatile("fence.proxy.async.global;" ::: "memory");
        if (lane == 0) issue_stage(i);
      }
    }
    const float SC = 0.08838834764831845f * 1.4426950408889634f;
    int st = 0, stp = 0;
    for (int s = 0; s < NSEG; s++) {
      const uint32_t kv = sb + C_KVQ + st * KVQ_ST;
      uint32_t kb[4][4], va[4][4], vm[4];
      {
        const int l = fresh(lane);
        const uint32_t k_l = (8 * w + (l & 7)) * 256 + (((l >> 3) ^ (l & 7)) << 4);
        const uint32_t q_l = 16384 + (l & 15) * 256 + (((l >> 4) ^ (l & 7)) << 4);
        mbar_wait(sb + MB_KVQ + 8 * st, stp);
        ldm4(kb[0], kv + k_l + j * 128); ldm4(kb[1], kv + (k_l ^ 64) + j * 128);
        ldm4(kb[2], kv + k_l + (j ^ 1) * 128); ldm4(kb[3], kv + (k_l ^ 64) + (j ^ 1) * 128);
        float s0[4], s1[4];
#pragma unroll
        for (int i = 0; i < 4; i++) {
          uint32_t a[4], c[4];
          const uint32_t qa = kv + ((i >> 1) ^ j) * 128;
          ldm4(a, qa + (q_l ^ ((i & 1) << 6)));
          ldm4(c, qa + (q_l ^ (((i & 1) << 6) | 32)));
          if (i == 0) { mma16z(s0, a[0], a[1], a[2], a[3], kb[i][0], kb[i][1]); mma16z(s1, c[0], c[1], c[2], c[3], kb[i][2], kb[i][3]); }
          else { mma16(s0, a[0], a[1], a[2], a[3], kb[i][0], kb[i][1]); mma16(s1, c[0], c[1], c[2], c[3], kb[i][2], kb[i][3]); }
        }
        const float NEG = -1.0e9f * 1.4426950408889634f;
        const int r = 16 * j + (l >> 2) - 2 * (l & 3) - 8 * w;
        asm volatile("st.shared.v4.f32 [%0], {%1,%2,%3,%4};" :: "r"(sb + C_S2 + w * 512 + l * 16), "f"(r >= 0 ? (s0[0] + s1[0]) * SC : NEG),
                     "f"(r >= 1 ? (s0[1] + s1[1]) * SC : NEG), "f"(r >= -8 ? (s0[2] + s1[2]) * SC : NEG), "f"(r >= -7 ? (s0[3] + s1[3]) * SC : NEG) : "memory");
      }
      const int lq = fresh(lane);
      uint32_t qm = sb + C_QM + (s & 1) * QM_BUF + (lq ^ (((lq >> 3) & 3) << 1)) * 16;
      asm volatile("" : "+r"(qm));
      auto load_va = [&]() {
        const int l = fresh(lane);
        const uint32_t v_l = kv + 8192 + ((l & 7) + ((l >> 4) << 3)) * 256 + (w >> 1) * 128;
        const uint32_t ch = (((w & 1) * 4 + ((l >> 3) & 1)) ^ (l & 7)) << 4;
        ldm4t(va[0], v_l + ch); ldm4t(va[1], v_l + ch + 4096); ldm4t(va[2], v_l + (ch ^ 32)); ldm4t(va[3], v_l + (ch ^ 32) + 4096);
      };
      if (s < NSEG - 1) {
        STAMP(13);
        bar_sync<6, 384>();
        STAMP2(8);
        float s0[4], s1[4];
        uint32_t q0[4], q1[4], k0[4], k1[4];
        ldm4t(q0, qm + j * 1024); ldm4t(k0, qm + 2048 + j * 1024); ldm4t(q1, qm + j * 1024 + 512); ldm4t(k1, qm + 2048 + j * 1024 + 512);
        mma16z(s0, kb[0][0], k0[0], kb[0][1], k0[1], q0[0], q0[1]);
        mma16z(s1, kb[0][2], k0[2], kb[0][3], k0[3], q0[2], q0[3]);
        mma16(s0, kb[1][0], k1[0], kb[1][1], k1[1], q1[0], q1[1]);
        mma16(s1, kb[1][2], k1[2], kb[1][3], k1[3], q1[2], q1[3]);
        const int l = fresh(lane);
        const uint4 ma = lds128(sb + C_MX), mb = lds128(sb + C_MX + 16);
        int E = (int)max(max(max(max(ma.x, ma.y), max(ma.z, ma.w)), max(max(mb.x, mb.y), max(mb.z, mb.w))) >> 7, lds32(sb + C_XE + s * 4)) + wexp;
        E = min(max(E, -100), 100);
        load_va();
#pragma unroll
        for (int i = 0; i < 4; i++) s0[i] += s1[i];
        uint32_t sx_st = sb + C_SX + (l & 3) * 384 + (l >> 3) * 48 + ((l >> 2) & 1) * 4;
        asm volatile("" : "+r"(sx_st));
        mbar_wait_cluster(sb + MB_PEER + (s & 1) * 8, (s >> 1) & 1);
        STAMP(9);
        ldm4t(q0, qm + (j ^ 1) * 1024); ldm4t(k0, qm + 2048 + (j ^ 1) * 1024);
        ldm4t(q1, qm + (j ^ 1) * 1024 + 512); ldm4t(k1, qm + 2048 + (j ^ 1) * 1024 + 512);
        mma16(s0, kb[2][0], k0[0], kb[2][1], k0[1], q0[0], q0[1]);
        mma16z(s1, kb[2][2], k0[2], kb[2][3], k0[3], q0[2], q0[3]);
        mma16(s0, kb[3][0], k1[0], kb[3][1], k1[1], q1[0], q1[1]);
        mma16(s1, kb[3][2], k1[2], kb[3][3], k1[3], q1[2], q1[3]);
        ldm4(vm, qm + 4096 + w * 512);
        const int lc = fresh(lane);
        uint32_t ot_st = sb + C_OT + (32 * w + 8 * ((lc & 7) >> 1) + ((2 * (lc >> 3)) ^ (lc & 6)) + (lc & 1)) * 16;
        uint32_t sx_ld = sb + C_SX + lc * 48;
        asm volatile("" : "+r"(ot_st), "+r"(sx_ld));
        sts32(sx_st + w * 8, __float_as_uint(s0[0] + s1[0]));
        sts32(sx_st + w * 8 + 192, __float_as_uint(s0[1] + s1[1]));
        sts32(sx_st + 32 + (w & 1) * 192, __float_as_uint((w & 1) ? s0[3] + s1[3] : s0[2] + s1[2]));
        bar_sync<8, 128>();
        const uint4 u0 = lds128(sx_ld), u1 = lds128(sx_ld + 16);
        const float2 u2 = lds64f(sx_ld + 32);
        float sv[10] = {__uint_as_float(u0.x), __uint_as_float(u0.y), __uint_as_float(u0.z), __uint_as_float(u0.w), __uint_as_float(u1.x),
                        __uint_as_float(u1.y), __uint_as_float(u1.z), __uint_as_float(u1.w), u2.x, u2.y};
        float m = fmaxf(fmaxf(fmaxf(sv[0], sv[1]), fmaxf(sv[2], sv[3])), fmaxf(fmaxf(sv[4], sv[5]), fmaxf(sv[6], sv[7])));
        m = fmaxf(m, fmaxf(sv[8], sv[9]));
        m = fmaxf(m, __shfl_xor_sync(~0u, m, 1));
        m = fmaxf(m, __shfl_xor_sync(~0u, m, 2));
        m *= -SC;
        uint32_t p[5];
#pragma unroll
        for (int i = 0; i < 5; i++) p[i] = pack_bf16(ex2(fmaf(sv[2 * i], SC, m)), ex2(fmaf(sv[2 * i + 1], SC, m)));
        float o0[4], o1[4], su[4];
        const uint32_t ONE = 0x3F803F80u;
        mma16z(su, ONE, ONE, ONE, ONE, p[0], p[1]);
        mma16z(o0, va[0][0], va[0][1], va[0][2], va[0][3], p[0], p[1]);
        mma16z(o1, va[2][0], va[2][1], va[2][2], va[2][3], p[0], p[1]);
        mma16(su, ONE, ONE, ONE, ONE, p[2], p[3]);
        mma16(o0, va[1][0], va[1][1], va[1][2], va[1][3], p[2], p[3]);
        mma16(o1, va[3][0], va[3][1], va[3][2], va[3][3], p[2], p[3]);
        mma8(su, ONE, ONE, p[4]);
        mma8(o0, vm[0], vm[1], p[4]);
        mma8(o1, vm[2], vm[3], p[4]);
        const float dn = __uint_as_float((uint32_t)(127 - E) << 23);
        sts32(sb + C_SC, (uint32_t)(127 + E) << 23);
        float r0, r1;
        asm("rcp.approx.ftz.f32 %0, %1;" : "=f"(r0) : "f"(su[0]));
        asm("rcp.approx.ftz.f32 %0, %1;" : "=f"(r1) : "f"(su[1]));
        r0 *= dn; r1 *= dn;
        stm4(ot_st, pack_bf16(o0[0] * r0, o0[1] * r1), pack_bf16(o0[2] * r0, o0[3] * r1), pack_bf16(o1[0] * r0, o1[1] * r1), pack_bf16(o1[2] * r0, o1[3] * r1));
        bar_arrive<7, 384>();
        STAMP(10);
        if (w == 0 && lc == 0) mbar_expect_tx(sb + MB_PEER + (s & 1) * 8, 3072);
        if (w == 1) {
          fence_gpu();
          if (lc == 0 && s > 0) red_relaxed(g_fo + 2 * (s - 1) + j);
        }
        bar_sync<9, 384>();
      } else {
        load_va();
        bar_sync<6, 384>();
        mbar_wait_cluster(sb + MB_PEER + (s & 1) * 8, (s >> 1) & 1);
        ldm4(vm, qm + 4096 + w * 512);
        bar_sync<8, 128>();
      }
      STAMP2(11);
      {
        const int l = fresh(lane), g = l >> 2, t = l & 3;
        const uint32_t q_l = 16384 + (l & 15) * 256 + (((l >> 4) ^ (l & 7)) << 4);
        const int tok = s * SEGL + 16 * j + g;
        float sc[5][4], s1[4];
#pragma unroll
        for (int i = 0; i < 4; i++) {
          uint32_t km[4], a[4], c[4];
          ldm4t(km, qm + 2048 + i * 512);
          const uint32_t qa = kv + (i >> 1) * 128;
          ldm4(a, qa + (q_l ^ ((i & 1) << 6)));
          ldm4(c, qa + (q_l ^ (((i & 1) << 6) | 32)));
          if (i == 0) { mma16z(sc[4], a[0], a[1], a[2], a[3], km[0], km[1]); mma16z(s1, c[0], c[1], c[2], c[3], km[2], km[3]); }
          else { mma16(sc[4], a[0], a[1], a[2], a[3], km[0], km[1]); mma16(s1, c[0], c[1], c[2], c[3], km[2], km[3]); }
        }
#pragma unroll
        for (int i = 0; i < 4; i++) {
          const uint4 u = lds128(sb + C_S2 + i * 512 + l * 16);
          sc[i][0] = __uint_as_float(u.x); sc[i][1] = __uint_as_float(u.y); sc[i][2] = __uint_as_float(u.z); sc[i][3] = __uint_as_float(u.w);
          sc[4][i] = (sc[4][i] + s1[i]) * SC;
        }
        float m0 = -INFINITY, m1 = -INFINITY;
#pragma unroll
        for (int i = 0; i < 5; i++) {
          m0 = fmaxf(m0, fmaxf(sc[i][0], sc[i][1]));
          m1 = fmaxf(m1, fmaxf(sc[i][2], sc[i][3]));
        }
        m0 = fmaxf(m0, __shfl_xor_sync(~0u, m0, 1)); m0 = fmaxf(m0, __shfl_xor_sync(~0u, m0, 2));
        m1 = fmaxf(m1, __shfl_xor_sync(~0u, m1, 1)); m1 = fmaxf(m1, __shfl_xor_sync(~0u, m1, 2));
        float s0 = 0.f, s2 = 0.f;
        uint32_t p[5][2];
#pragma unroll
        for (int i = 0; i < 5; i++) {
          const float e0 = ex2(sc[i][0] - m0), e1 = ex2(sc[i][1] - m0), e2 = ex2(sc[i][2] - m1), e3 = ex2(sc[i][3] - m1);
          s0 += e0 + e1; s2 += e2 + e3;
          p[i][0] = pack_bf16(e0, e1); p[i][1] = pack_bf16(e2, e3);
        }
        s0 += __shfl_xor_sync(~0u, s0, 1); s0 += __shfl_xor_sync(~0u, s0, 2);
        s2 += __shfl_xor_sync(~0u, s2, 1); s2 += __shfl_xor_sync(~0u, s2, 2);
        float o[4][4];
#pragma unroll
        for (int i = 0; i < 4; i++) {
          mma8z(o[i], p[4][0], p[4][1], vm[i]);
          mma16(o[i], p[0][0], p[0][1], p[1][0], p[1][1], va[i & 2][i & 1], va[i & 2][(i & 1) + 2]);
          mma16(o[i], p[2][0], p[2][1], p[3][0], p[3][1], va[(i & 2) + 1][i & 1], va[(i & 2) + 1][(i & 1) + 2]);
        }
        float r0, r1;
        asm("rcp.approx.ftz.f32 %0, %1;" : "=f"(r0) : "f"(s0));
        asm("rcp.approx.ftz.f32 %0, %1;" : "=f"(r1) : "f"(s2));
        r0 *= __uint_as_float(lds32(sb + C_GT + st * 64 + g * 4)); r1 *= __uint_as_float(lds32(sb + C_GT + st * 64 + 32 + g * 4));
        bf16* op = g_a + (size_t)tok * KA + h * DH + 32 * w + 8 * t;
        *reinterpret_cast<uint4*>(op) = make_uint4(pack_bf16(o[0][0] * r0, o[0][1] * r0), pack_bf16(o[1][0] * r0, o[1][1] * r0),
                                                   pack_bf16(o[2][0] * r0, o[2][1] * r0), pack_bf16(o[3][0] * r0, o[3][1] * r0));
        *reinterpret_cast<uint4*>(op + 8 * KA) = make_uint4(pack_bf16(o[0][2] * r1, o[0][3] * r1), pack_bf16(o[1][2] * r1, o[1][3] * r1),
                                                            pack_bf16(o[2][2] * r1, o[2][3] * r1), pack_bf16(o[3][2] * r1, o[3][3] * r1));
      }
      if (w == 1 && s >= 2) {
        const int u = cta * 10 + fresh(lane);
        if (u < cta * 10 + 10) *reinterpret_cast<uint4*>(g_ring + ((s - 2) & 7) * RING_SLOT + (u >> 3) * 256 + (u & 7) * 16) = make_uint4(0, 0, 0, 0);
      }
      bar_sync<8, 128>();
      STAMP2(12);
      STAMP_NEXT;
      if (++st == 3) { st = 0; stp ^= 1; }
    }
    if (w == 1 && lane == 0) {
      fence_gpu();
      red_relaxed(g_fo + 2 * (NSEG - 2) + j);
      red_relaxed(g_fo + 2 * (NSEG - 1) + j);
    }
    if (w == 0 && lane == 0) atomicAdd(&g_done, 1u);
  }
}

typedef CUresult (*EncodeFn)(CUtensorMap*, CUtensorMapDataType, cuuint32_t, void*, const cuuint64_t*, const cuuint64_t*, const cuuint32_t*,
                             const cuuint32_t*, CUtensorMapInterleave, CUtensorMapSwizzle, CUtensorMapL2promotion, CUtensorMapFloatOOBfill);
static void make_map(EncodeFn enc, CUtensorMap* tm, const void* base, uint64_t cols, uint64_t rows, uint32_t bc, uint32_t br) {
  cuuint64_t dims[2] = {cols, rows};
  cuuint64_t strides[1] = {cols * 2};
  cuuint32_t box[2] = {bc, br}, es[2] = {1, 1};
  enc(tm, CU_TENSOR_MAP_DATA_TYPE_BFLOAT16, 2, const_cast<void*>(base), dims, strides, box, es, CU_TENSOR_MAP_INTERLEAVE_NONE,
      CU_TENSOR_MAP_SWIZZLE_128B, CU_TENSOR_MAP_L2_PROMOTION_L2_256B, CU_TENSOR_MAP_FLOAT_OOB_FILL_NONE);
}

static int make_map5(EncodeFn enc, CUtensorMap* tm, const void* base, uint64_t cols, uint64_t rows, uint32_t groups, bool regroup) {
  const uint64_t rb = cols * 2;
  cuuint64_t dims[5] = {cols, 2, 4, 4, rows / 32};
  cuuint64_t strides[4] = {rb, (regroup ? 8 : 2) * rb, (regroup ? 2 : 8) * rb, 32 * rb};
  cuuint32_t box[5] = {64, 2, 4, 4, groups}, es[5] = {1, 1, 1, 1, 1};
  return (int)enc(tm, CU_TENSOR_MAP_DATA_TYPE_BFLOAT16, 5, const_cast<void*>(base), dims, strides, box, es, CU_TENSOR_MAP_INTERLEAVE_NONE,
                  CU_TENSOR_MAP_SWIZZLE_128B, CU_TENSOR_MAP_L2_PROMOTION_L2_256B, CU_TENSOR_MAP_FLOAT_OOB_FILL_NONE);
}

#define EST_STEP 4300.0
static void build_schedule(Args& a) {
  struct J { uint32_t code; int kind, p, n; double dur; bool done; };
  static J jobs[MAXJOBS];
  int nj = 0;
  const double KS = 1100.0, T0 = 12000.0, TQ = 115000.0;
  const int split[8] = {2, 2, 2, 2, 2, 2, 4, 16};
  for (int p = 0; p < 8; p++) for (int n = 0; n < 14; n++) jobs[nj++] = J{(uint32_t)(p << 1 | n << 4 | 8 << 15), 0, p, n, 8 * KS + 400, false};
  for (int p = 0; p < 8; p++) for (int n = 0; n < 2; n++)
    jobs[nj++] = J{(uint32_t)(1 | p << 1 | n << 4 | 64 << 8 | 28 << 15 | 1 << 22 | (split[p] + 1) << 23), 1, p, n, 28 * KS + 600, false};
  for (int p = 0; p < 8; p++) for (int q = 0; q < split[p]; q++) for (int n = 0; n < 2; n++) {
    const int nk = 64 / split[p];
    jobs[nj++] = J{(uint32_t)(1 | p << 1 | n << 4 | (q * nk) << 8 | nk << 15 | (split[p] + 1) << 23), 2, p, n, nk * KS + 1000, false};
  }
  double avail[NGC], hready[8] = {}, sready[16];
  int hleft[8]; bool sset[16] = {};
  static uint32_t lists[NGC][MAXJOBS]; int cnt[NGC] = {};
  for (int p = 0; p < 8; p++) hleft[p] = 14;
  for (int c = 0; c < NGC; c++) avail[c] = c < 32 ? TQ : 3000.0;
  for (int done = 0; done < nj; done++) {
    int c = 0;
    for (int i = 1; i < NGC; i++) if (avail[i] < avail[c]) c = i;
    int best = -1; double bt = 1e30;
    for (int i = 0; i < nj; i++) {
      J& q = jobs[i];
      if (q.done) continue;
      double r = 0;
      if (q.kind == 1) { if (hleft[q.p]) continue; r = hready[q.p]; }
      if (q.kind == 2) {
        if (!sset[q.p * 2 + q.n]) continue;
        r = T0 + (8 * q.p + 9) * EST_STEP;
        if (sready[q.p * 2 + q.n] - q.dur > r) r = sready[q.p * 2 + q.n] - q.dur;
      }
      if (r < avail[c]) r = avail[c];
      if (r < bt) { bt = r; best = i; }
    }
    J& q = jobs[best];
    q.done = true;
    avail[c] = bt + q.dur;
    lists[c][cnt[c]++] = q.code;
    if (q.kind == 0) { hleft[q.p]--; if (avail[c] > hready[q.p]) hready[q.p] = avail[c]; }
    if (q.kind == 1) { sset[q.p * 2 + q.n] = true; sready[q.p * 2 + q.n] = avail[c]; }
  }
  int o = 0;
  for (int c = 0; c < NGC; c++) { a.first[c] = (uint16_t)o; for (int i = 0; i < cnt[c]; i++) a.job[o++] = lists[c][i]; }
  a.first[NGC] = (uint16_t)o; a.first[NGC + 1] = 0; a.zero = 0;
  for (; o < MAXJOBS; o++) a.job[o] = 0;
}

extern "C" void kernel_launch(void* const* d_in, const int* in_sizes, int n_in, void* d_out, int out_size) {
  (void)in_sizes; (void)n_in; (void)out_size;
  const bf16 *wq = (const bf16*)d_in[2], *wk = (const bf16*)d_in[3], *wv = (const bf16*)d_in[4], *wo = (const bf16*)d_in[5],
             *wg = (const bf16*)d_in[8], *wu = (const bf16*)d_in[9], *wd = (const bf16*)d_in[10];
  static EncodeFn enc = nullptr;
  static Args a;
  if (!enc) {
    void* fn = nullptr; cudaDriverEntryPointQueryResult qr;
    cudaGetDriverEntryPoint("cuTensorMapEncodeTiled", &fn, cudaEnableDefault, &qr);
    enc = (EncodeFn)fn;
    cudaFuncSetAttribute(fused_kernel, cudaFuncAttributeMaxDynamicSharedMemorySize, K_SMEM);
    build_schedule(a);
  }
  make_map(enc, &a.tmq, wq, HD, DM, 64, 256); make_map(enc, &a.tmk, wk, HD, DM, 64, 256); make_map(enc, &a.tmv, wv, HD, DM, 64, 256);
  make_map(enc, &a.tmo, wo, DM, HD, 64, 128);
  int rc = make_map5(enc, &a.pw[0], wk, HD, DM, 4, true) | make_map5(enc, &a.pw[1], wv, HD, DM, 4, true) | make_map5(enc, &a.pw[2], wq, HD, DM, 4, true) |
           make_map5(enc, &a.pb[0], wg, FF, DM, 2, true) | make_map5(enc, &a.pb[1], wu, FF, DM, 2, true) |
           make_map5(enc, &a.pb[2], wo, DM, HD, 2, true) | make_map5(enc, &a.pb[3], wd, DM, FF, 2, false);
  if (rc) return;
  a.x = (const bf16*)d_in[0]; a.mem0 = (const bf16*)d_in[1]; a.wo = wo; a.gate_w = (const bf16*)d_in[11]; a.out = (bf16*)d_out;
  cudaLaunchConfig_t cfg = {};
  cfg.gridDim = dim3(NCTA); cfg.blockDim = dim3(384); cfg.dynamicSmemBytes = K_SMEM; cfg.stream = cudaStreamPerThread;
  cudaLaunchAttribute at[1];
  at[0].id = cudaLaunchAttributeClusterDimension; at[0].val.clusterDim.x = 2; at[0].val.clusterDim.y = 1; at[0].val.clusterDim.z = 1;
  cfg.attrs = at; cfg.numAttrs = 1;
  cudaLaunchKernelEx(&cfg, fused_kernel, a);
}
```

```cpp
#include <cuda_runtime.h>
#include <cuda_bf16.h>
#include <cuda_fp16.h>
#include <cuda.h>
#include <stdint.h>

typedef __nv_bfloat16 bf16;
#define FAT_REGS "224"
#define AUX_REGS "56"
#ifndef NVQ
#define NVQ 3
#endif
#define WO_EARLY 12
#define WO_PAR 2
#define WV_A 8
#define FLAG_O red_release
#define POLL_DELAY 8

constexpr int SEQ = 2048, DM = 512, NH = 32, DH = 128, SEGL = 32, NSEG = 64, FF = 1792;
constexpr int HD = NH * DH;
constexpr int KA = HD + FF;
constexpr int NCTA = 132, NGC = 34, MAXJOBS = 320;
constexpr int BLK_BYTES = 24576;
constexpr int RING_SLOT = 32768;
constexpr int A_TILE = KA / 32 * 1024;
constexpr int SPIN_LIMIT = 1 << 20;

__device__ __align__(1024) uint8_t g_qkv[(size_t)NSEG * NH * BLK_BYTES];
__device__ __align__(1024) uint8_t g_a[(size_t)SEQ * KA * 2];
__device__ __align__(1024) float g_acc[(size_t)SEQ * DM];
__device__ unsigned g_fq[NSEG * NH];
__device__ unsigned g_fh[128];
__device__ unsigned g_fo[128];
__device__ unsigned g_fc[256];
__device__ __align__(1024) uint8_t g_ring[9 * RING_SLOT];
__device__ __align__(128) float g_gate[SEQ];
__device__ uint4 g_pub[64];
__device__ unsigned g_done;
__device__ int g_err;

__device__ __forceinline__ uint32_t smem_u32(const void* p) { return (uint32_t)__cvta_generic_to_shared(p); }
__device__ __forceinline__ uint32_t mapa(uint32_t a, uint32_t rank) { uint32_t r; asm volatile("mapa.shared::cluster.u32 %0, %1, %2;" : "=r"(r) : "r"(a), "r"(rank)); return r; }
__device__ __forceinline__ void mbar_init(uint32_t a, uint32_t cnt) { asm volatile("mbarrier.init.shared::cta.b64 [%0], %1;" :: "r"(a), "r"(cnt) : "memory"); }
__device__ __forceinline__ void mbar_expect_tx(uint32_t a, uint32_t bytes) { asm volatile("mbarrier.arrive.expect_tx.shared::cta.b64 _, [%0], %1;" :: "r"(a), "r"(bytes) : "memory"); }
__device__ __forceinline__ bool mbar_try(uint32_t a, uint32_t parity) {
  uint32_t ok;
  asm volatile("{ .reg .pred p; mbarrier.try_wait.parity.shared::cta.b64 p, [%1], %2; selp.u32 %0, 1, 0, p; }" : "=r"(ok) : "r"(a), "r"(parity) : "memory");
  return ok;
}
__device__ __forceinline__ bool mbar_try_cluster(uint32_t a, uint32_t parity) {
  uint32_t ok;
  asm volatile("{ .reg .pred p; mbarrier.try_wait.parity.acquire.cluster.shared::cta.b64 p, [%1], %2; selp.u32 %0, 1, 0, p; }" : "=r"(ok) : "r"(a), "r"(parity) : "memory");
  return ok;
}
__device__ __forceinline__ bool give_up(int it, int code) {
  if ((it & 1023) != 0) return false;
  if (it < SPIN_LIMIT && *reinterpret_cast<volatile int*>(&g_err) == 0) return false;
  if (it >= SPIN_LIMIT) g_err = code;
  return true;
}
__device__ __forceinline__ void mbar_wait(uint32_t a, uint32_t parity) {
  int it = 0;
  while (!mbar_try(a, parity)) { if (give_up(++it, 1)) break; }
}
__device__ __forceinline__ void mbar_wait_cluster(uint32_t a, uint32_t parity) {
  int it = 0;
  while (!mbar_try_cluster(a, parity)) { if (give_up(++it, 2)) break; }
}
template <int ID, int N> __device__ __forceinline__ void bar_sync() { asm volatile("bar.sync %0, %1;" :: "n"(ID), "n"(N) : "memory"); }
template <int ID, int N> __device__ __forceinline__ void bar_arrive() { asm volatile("bar.arrive %0, %1;" :: "n"(ID), "n"(N) : "memory"); }
__device__ __forceinline__ void bar_sync_id(int id, int n) { asm volatile("bar.sync %0, %1;" :: "r"(id), "r"(n) : "memory"); }
__device__ __forceinline__ void tma2d(uint32_t dst, const CUtensorMap* tm, int c0, int c1, uint32_t mb) {
  asm volatile("cp.async.bulk.tensor.2d.shared::cluster.global.mbarrier::complete_tx::bytes [%0], [%1, {%3, %4}], [%2];"
               :: "r"(dst), "l"((uint64_t)tm), "r"(mb), "r"(c0), "r"(c1) : "memory");
}
__device__ __forceinline__ void bulk_g2s(uint32_t dst, const void* src, uint32_t bytes, uint32_t mb) {
  asm volatile("cp.async.bulk.shared::cluster.global.mbarrier::complete_tx::bytes [%0], [%1], %2, [%3];"
               :: "r"(dst), "l"(src), "r"(bytes), "r"(mb) : "memory");
}
__device__ __forceinline__ void ldm4(uint32_t* r, uint32_t a) {
  asm volatile("ldmatrix.sync.aligned.m8n8.x4.shared.b16 {%0,%1,%2,%3}, [%4];" : "=r"(r[0]), "=r"(r[1]), "=r"(r[2]), "=r"(r[3]) : "r"(a) : "memory");
}
__device__ __forceinline__ void ldm4t(uint32_t* r, uint32_t a) {
  asm volatile("ldmatrix.sync.aligned.m8n8.x4.trans.shared.b16 {%0,%1,%2,%3}, [%4];" : "=r"(r[0]), "=r"(r[1]), "=r"(r[2]), "=r"(r[3]) : "r"(a) : "memory");
}
__device__ __forceinline__ void stm4(uint32_t a, uint32_t r0, uint32_t r1, uint32_t r2, uint32_t r3) {
  asm volatile("stmatrix.sync.aligned.m8n8.x4.shared.b16 [%0], {%1,%2,%3,%4};" :: "r"(a), "r"(r0), "r"(r1), "r"(r2), "r"(r3) : "memory");
}
__device__ __forceinline__ void mma16(float* d, uint32_t a0, uint32_t a1, uint32_t a2, uint32_t a3, uint32_t b0, uint32_t b1) {
  asm volatile("mma.sync.aligned.m16n8k16.row.col.f32.bf16.bf16.f32 {%0,%1,%2,%3}, {%4,%5,%6,%7}, {%8,%9}, {%0,%1,%2,%3};"
               : "+f"(d[0]), "+f"(d[1]), "+f"(d[2]), "+f"(d[3]) : "r"(a0), "r"(a1), "r"(a2), "r"(a3), "r"(b0), "r"(b1));
}
__device__ __forceinline__ void mma16z(float* d, uint32_t a0, uint32_t a1, uint32_t a2, uint32_t a3, uint32_t b0, uint32_t b1) {
  asm volatile("mma.sync.aligned.m16n8k16.row.col.f32.bf16.bf16.f32 {%0,%1,%2,%3}, {%4,%5,%6,%7}, {%8,%9}, {%10,%10,%10,%10};"
               : "=f"(d[0]), "=f"(d[1]), "=f"(d[2]), "=f"(d[3]) : "r"(a0), "r"(a1), "r"(a2), "r"(a3), "r"(b0), "r"(b1), "f"(0.f));
}
__device__ __forceinline__ void mma8(float* d, uint32_t a0, uint32_t a1, uint32_t b0) {
  asm volatile("mma.sync.aligned.m16n8k8.row.col.f32.bf16.bf16.f32 {%0,%1,%2,%3}, {%4,%5}, {%6}, {%0,%1,%2,%3};"
               : "+f"(d[0]), "+f"(d[1]), "+f"(d[2]), "+f"(d[3]) : "r"(a0), "r"(a1), "r"(b0));
}
__device__ __forceinline__ void mma8z(float* d, uint32_t a0, uint32_t a1, uint32_t b0) {
  asm volatile("mma.sync.aligned.m16n8k8.row.col.f32.bf16.bf16.f32 {%0,%1,%2,%3}, {%4,%5}, {%6}, {%7,%7,%7,%7};"
               : "=f"(d[0]), "=f"(d[1]), "=f"(d[2]), "=f"(d[3]) : "r"(a0), "r"(a1), "r"(b0), "f"(0.f));
}
__device__ __forceinline__ uint32_t pack_bf16(float lo, float hi) { uint32_t r; asm("cvt.rn.bf16x2.f32 %0, %1, %2;" : "=r"(r) : "f"(hi), "f"(lo)); return r; }
__device__ __forceinline__ uint32_t pack_f16(float lo, float hi) { uint32_t r; asm("cvt.rn.f16x2.f32 %0, %1, %2;" : "=r"(r) : "f"(hi), "f"(lo)); return r; }
__device__ __forceinline__ float2 unpack_f16(uint32_t v) { return __half22float2(*reinterpret_cast<__half2*>(&v)); }
__device__ __forceinline__ uint32_t absmax2(uint32_t a, uint32_t b) { uint32_t r; asm("max.xorsign.abs.bf16x2 %0, %1, %2;" : "=r"(r) : "r"(a), "r"(b)); return r; }
__device__ __forceinline__ uint32_t fold_absmax(uint32_t m) { m &= 0x7FFF7FFFu; return max(m & 0xFFFFu, m >> 16); }
__device__ __forceinline__ float ex2(float x) { float r; asm("ex2.approx.ftz.f32 %0, %1;" : "=f"(r) : "f"(x)); return r; }
__device__ __forceinline__ void sts32(uint32_t a, uint32_t v) { asm volatile("st.shared.u32 [%0], %1;" :: "r"(a), "r"(v) : "memory"); }
__device__ __forceinline__ void sts64f(uint32_t a, float x, float y) { asm volatile("st.shared.v2.f32 [%0], {%1,%2};" :: "r"(a), "f"(x), "f"(y) : "memory"); }
__device__ __forceinline__ float2 lds64f(uint32_t a) { float2 v; asm volatile("ld.shared.v2.f32 {%0,%1}, [%2];" : "=f"(v.x), "=f"(v.y) : "r"(a) : "memory"); return v; }
__device__ __forceinline__ uint32_t lds32(uint32_t a) { uint32_t v; asm volatile("ld.shared.u32 %0, [%1];" : "=r"(v) : "r"(a) : "memory"); return v; }
__device__ __forceinline__ uint4 lds128(uint32_t a) { uint4 v; asm volatile("ld.shared.v4.u32 {%0,%1,%2,%3}, [%4];" : "=r"(v.x), "=r"(v.y), "=r"(v.z), "=r"(v.w) : "r"(a) : "memory"); return v; }
__device__ __forceinline__ void st_async32(uint32_t a, uint32_t v, uint32_t mb) {
  asm volatile("st.async.weak.shared::cluster.mbarrier::complete_tx::bytes.b32 [%0], %1, [%2];" :: "r"(a), "r"(v), "r"(mb) : "memory");
}
__device__ __forceinline__ void st_async64(uint32_t a, uint32_t x, uint32_t y, uint32_t mb) {
  asm volatile("st.async.weak.shared::cluster.mbarrier::complete_tx::bytes.v2.b32 [%0], {%1,%2}, [%3];" :: "r"(a), "r"(x), "r"(y), "r"(mb) : "memory");
}
__device__ __forceinline__ void st_async128(uint32_t a, uint32_t x, uint32_t y, uint32_t z, uint32_t w, uint32_t mb) {
  asm volatile("st.async.weak.shared::cluster.mbarrier::complete_tx::bytes.v4.b32 [%0], {%1,%2,%3,%4}, [%5];" :: "r"(a), "r"(x), "r"(y), "r"(z), "r"(w), "r"(mb) : "memory");
}
__device__ __forceinline__ void sts128(uint32_t a, uint32_t x, uint32_t y, uint32_t z, uint32_t w) {
  asm volatile("st.shared.v4.u32 [%0], {%1,%2,%3,%4};" :: "r"(a), "r"(x), "r"(y), "r"(z), "r"(w) : "memory");
}
__device__ __forceinline__ void lds128r(uint32_t* r, uint32_t a) {
  asm volatile("ld.shared.v4.u32 {%0,%1,%2,%3}, [%4];" : "=r"(r[0]), "=r"(r[1]), "=r"(r[2]), "=r"(r[3]) : "r"(a) : "memory");
}
__device__ __forceinline__ float4 lds128f(uint32_t a) { float4 v; asm volatile("ld.shared.v4.f32 {%0,%1,%2,%3}, [%4];" : "=f"(v.x), "=f"(v.y), "=f"(v.z), "=f"(v.w) : "r"(a) : "memory"); return v; }
__device__ __forceinline__ void mbar_arrive(uint32_t a) { asm volatile("mbarrier.arrive.shared::cta.b64 _, [%0];" :: "r"(a) : "memory"); }
__device__ __forceinline__ uint32_t movm(uint32_t a) { uint32_t d; asm volatile("movmatrix.sync.aligned.m8n8.trans.b16 %0, %1;" : "=r"(d) : "r"(a)); return d; }
__device__ __forceinline__ float rcp(float x) { float r; asm("rcp.approx.ftz.f32 %0, %1;" : "=f"(r) : "f"(x)); return r; }
__device__ __forceinline__ uint32_t f16_to_bf16(uint32_t v) { const float2 f = unpack_f16(v); return pack_bf16(f.x, f.y); }
__device__ __forceinline__ uint4 ldv128(const void* p) {
  uint4 v; asm volatile("ld.volatile.global.v4.u32 {%0,%1,%2,%3}, [%4];" : "=r"(v.x), "=r"(v.y), "=r"(v.z), "=r"(v.w) : "l"(p) : "memory"); return v;
}
__device__ __forceinline__ uint32_t ldv32(const void* p) { uint32_t v; asm volatile("ld.volatile.global.u32 %0, [%1];" : "=r"(v) : "l"(p) : "memory"); return v; }
__device__ __forceinline__ float bf_lo(uint32_t v) { return __uint_as_float(v << 16); }
__device__ __forceinline__ float bf_hi(uint32_t v) { return __uint_as_float(v & 0xFFFF0000u); }

__device__ __forceinline__ void wgmma_rs192(float* d, uint32_t a0, uint32_t a1, uint32_t a2, uint32_t a3, uint64_t desc, int acc) {
  asm volatile("{ .reg .pred p; setp.ne.b32 p, %101, 0;\n"
    "wgmma.mma_async.sync.aligned.m64n192k16.f32.bf16.bf16 {%0,%1,%2,%3,%4,%5,%6,%7,%8,%9,%10,%11,%12,%13,%14,%15,%16,%17,%18,%19,%20,%21,%22,%23,%24,%25,%26,%27,%28,%29,%30,%31,%32,%33,%34,%35,%36,%37,%38,%39,%40,%41,%42,%43,%44,%45,%46,%47,%48,%49,%50,%51,%52,%53,%54,%55,%56,%57,%58,%59,%60,%61,%62,%63,%64,%65,%66,%67,%68,%69,%70,%71,%72,%73,%74,%75,%76,%77,%78,%79,%80,%81,%82,%83,%84,%85,%86,%87,%88,%89,%90,%91,%92,%93,%94,%95}, {%96,%97,%98,%99}, %100, p, 1, 1, 1; }"
    :
      "+f"(d[0]), "+f"(d[1]), "+f"(d[2]), "+f"(d[3]), "+f"(d[4]), "+f"(d[5]), "+f"(d[6]), "+f"(d[7]), "+f"(d[8]), "+f"(d[9]), "+f"(d[10]), "+f"(d[11]),
      "+f"(d[12]), "+f"(d[13]), "+f"(d[14]), "+f"(d[15]), "+f"(d[16]), "+f"(d[17]), "+f"(d[18]), "+f"(d[19]), "+f"(d[20]), "+f"(d[21]), "+f"(d[22]), "+f"(d[23]),
      "+f"(d[24]), "+f"(d[25]), "+f"(d[26]), "+f"(d[27]), "+f"(d[28]), "+f"(d[29]), "+f"(d[30]), "+f"(d[31]), "+f"(d[32]), "+f"(d[33]), "+f"(d[34]), "+f"(d[35]),
      "+f"(d[36]), "+f"(d[37]), "+f"(d[38]), "+f"(d[39]), "+f"(d[40]), "+f"(d[41]), "+f"(d[42]), "+f"(d[43]), "+f"(d[44]), "+f"(d[45]), "+f"(d[46]), "+f"(d[47]),
      "+f"(d[48]), "+f"(d[49]), "+f"(d[50]), "+f"(d[51]), "+f"(d[52]), "+f"(d[53]), "+f"(d[54]), "+f"(d[55]), "+f"(d[56]), "+f"(d[57]), "+f"(d[58]), "+f"(d[59]),
      "+f"(d[60]), "+f"(d[61]), "+f"(d[62]), "+f"(d[63]), "+f"(d[64]), "+f"(d[65]), "+f"(d[66]), "+f"(d[67]), "+f"(d[68]), "+f"(d[69]), "+f"(d[70]), "+f"(d[71]),
      "+f"(d[72]), "+f"(d[73]), "+f"(d[74]), "+f"(d[75]), "+f"(d[76]), "+f"(d[77]), "+f"(d[78]), "+f"(d[79]), "+f"(d[80]), "+f"(d[81]), "+f"(d[82]), "+f"(d[83]),
      "+f"(d[84]), "+f"(d[85]), "+f"(d[86]), "+f"(d[87]), "+f"(d[88]), "+f"(d[89]), "+f"(d[90]), "+f"(d[91]), "+f"(d[92]), "+f"(d[93]), "+f"(d[94]), "+f"(d[95])
    : "r"(a0), "r"(a1), "r"(a2), "r"(a3), "l"(desc), "r"(acc));
}

__device__ __forceinline__ void wgmma_rs256(float* d, uint32_t a0, uint32_t a1, uint32_t a2, uint32_t a3, uint64_t desc, int acc) {
  asm volatile("{ .reg .pred p; setp.ne.b32 p, %133, 0;\n"
    "wgmma.mma_async.sync.aligned.m64n256k16.f32.bf16.bf16 {%0,%1,%2,%3,%4,%5,%6,%7,%8,%9,%10,%11,%12,%13,%14,%15,%16,%17,%18,%19,%20,%21,%22,%23,%24,%25,%26,%27,%28,%29,%30,%31,%32,%33,%34,%35,%36,%37,%38,%39,%40,%41,%42,%43,%44,%45,%46,%47,%48,%49,%50,%51,%52,%53,%54,%55,%56,%57,%58,%59,%60,%61,%62,%63,%64,%65,%66,%67,%68,%69,%70,%71,%72,%73,%74,%75,%76,%77,%78,%79,%80,%81,%82,%83,%84,%85,%86,%87,%88,%89,%90,%91,%92,%93,%94,%95,%96,%97,%98,%99,%100,%101,%102,%103,%104,%105,%106,%107,%108,%109,%110,%111,%112,%113,%114,%115,%116,%117,%118,%119,%120,%121,%122,%123,%124,%125,%126,%127}, {%128,%129,%130,%131}, %132, p, 1, 1, 1; }"
    :
      "+f"(d[0]), "+f"(d[1]), "+f"(d[2]), "+f"(d[3]), "+f"(d[4]), "+f"(d[5]), "+f"(d[6]), "+f"(d[7]), "+f"(d[8]), "+f"(d[9]), "+f"(d[10]), "+f"(d[11]),
      "+f"(d[12]), "+f"(d[13]), "+f"(d[14]), "+f"(d[15]), "+f"(d[16]), "+f"(d[17]), "+f"(d[18]), "+f"(d[19]), "+f"(d[20]), "+f"(d[21]), "+f"(d[22]), "+f"(d[23]),
      "+f"(d[24]), "+f"(d[25]), "+f"(d[26]), "+f"(d[27]), "+f"(d[28]), "+f"(d[29]), "+f"(d[30]), "+f"(d[31]), "+f"(d[32]), "+f"(d[33]), "+f"(d[34]), "+f"(d[35]),
      "+f"(d[36]), "+f"(d[37]), "+f"(d[38]), "+f"(d[39]), "+f"(d[40]), "+f"(d[41]), "+f"(d[42]), "+f"(d[43]), "+f"(d[44]), "+f"(d[45]), "+f"(d[46]), "+f"(d[47]),
      "+f"(d[48]), "+f"(d[49]), "+f"(d[50]), "+f"(d[51]), "+f"(d[52]), "+f"(d[53]), "+f"(d[54]), "+f"(d[55]), "+f"(d[56]), "+f"(d[57]), "+f"(d[58]), "+f"(d[59]),
      "+f"(d[60]), "+f"(d[61]), "+f"(d[62]), "+f"(d[63]), "+f"(d[64]), "+f"(d[65]), "+f"(d[66]), "+f"(d[67]), "+f"(d[68]), "+f"(d[69]), "+f"(d[70]), "+f"(d[71]),
      "+f"(d[72]), "+f"(d[73]), "+f"(d[74]), "+f"(d[75]), "+f"(d[76]), "+f"(d[77]), "+f"(d[78]), "+f"(d[79]), "+f"(d[80]), "+f"(d[81]), "+f"(d[82]), "+f"(d[83]),
      "+f"(d[84]), "+f"(d[85]), "+f"(d[86]), "+f"(d[87]), "+f"(d[88]), "+f"(d[89]), "+f"(d[90]), "+f"(d[91]), "+f"(d[92]), "+f"(d[93]), "+f"(d[94]), "+f"(d[95]),
      "+f"(d[96]), "+f"(d[97]), "+f"(d[98]), "+f"(d[99]), "+f"(d[100]), "+f"(d[101]), "+f"(d[102]), "+f"(d[103]), "+f"(d[104]), "+f"(d[105]), "+f"(d[106]), "+f"(d[107]),
      "+f"(d[108]), "+f"(d[109]), "+f"(d[110]), "+f"(d[111]), "+f"(d[112]), "+f"(d[113]), "+f"(d[114]), "+f"(d[115]), "+f"(d[116]), "+f"(d[117]), "+f"(d[118]), "+f"(d[119]),
      "+f"(d[120]), "+f"(d[121]), "+f"(d[122]), "+f"(d[123]), "+f"(d[124]), "+f"(d[125]), "+f"(d[126]), "+f"(d[127])
    : "r"(a0), "r"(a1), "r"(a2), "r"(a3), "l"(desc), "r"(acc));
}

__device__ __forceinline__ void wg_fence() { asm volatile("wgmma.fence.sync.aligned;" ::: "memory"); }
__device__ __forceinline__ void wg_commit() { asm volatile("wgmma.commit_group.sync.aligned;" ::: "memory"); }
template <int N> __device__ __forceinline__ void wg_wait() { asm volatile("wgmma.wait_group.sync.aligned %0;" :: "n"(N) : "memory"); }
__device__ __forceinline__ void tma5d(uint32_t dst, const CUtensorMap* tm, int c0, int c4, uint32_t mb) {
  asm volatile("cp.async.bulk.tensor.5d.shared::cluster.global.mbarrier::complete_tx::bytes [%0], [%1, {%3, %5, %5, %5, %4}], [%2];"
               :: "r"(dst), "l"((uint64_t)tm), "r"(mb), "r"(c0), "r"(c4), "r"(0) : "memory");
}
__device__ __forceinline__ void tma5d_mc(uint32_t dst, const CUtensorMap* tm, int c0, int c4, uint32_t mb) {
  asm volatile("cp.async.bulk.tensor.5d.shared::cluster.global.mbarrier::complete_tx::bytes.multicast::cluster [%0], [%1, {%3, %5, %5, %5, %4}], [%2], %6;"
               :: "r"(dst), "l"((uint64_t)tm), "r"(mb), "r"(c0), "r"(c4), "r"(0), "h"((unsigned short)3) : "memory");
}
__device__ __forceinline__ void mbar_arrive_cluster(uint32_t a) { asm volatile("mbarrier.arrive.shared::cluster.b64 _, [%0];" :: "r"(a) : "memory"); }
__device__ __forceinline__ void ldg128(uint32_t* r, const uint8_t* p) {
  asm volatile("ld.global.L1::no_allocate.v4.u32 {%0,%1,%2,%3}, [%4];" : "=r"(r[0]), "=r"(r[1]), "=r"(r[2]), "=r"(r[3]) : "l"(p) : "memory");
}
__device__ __forceinline__ uint32_t ld_relaxed(const unsigned* p) { uint32_t v; asm volatile("ld.relaxed.gpu.global.u32 %0, [%1];" : "=r"(v) : "l"(p) : "memory"); return v; }
__device__ __forceinline__ uint32_t ld_acquire(const unsigned* p) { uint32_t v; asm volatile("ld.acquire.gpu.global.u32 %0, [%1];" : "=r"(v) : "l"(p) : "memory"); return v; }
__device__ __forceinline__ void red_release(unsigned* p) { asm volatile("red.release.gpu.global.add.u32 [%0], 1;" :: "l"(p) : "memory"); }
__device__ __forceinline__ void red_relaxed(unsigned* p) { asm volatile("red.relaxed.gpu.global.add.u32 [%0], 1;" :: "l"(p) : "memory"); }
__device__ __forceinline__ void fence_gpu() { asm volatile("fence.acq_rel.gpu;" ::: "memory"); }
__device__ __forceinline__ void wait_count(const unsigned* p, uint32_t target) {
  int it = 0;
  while (__any_sync(~0u, (int)(ld_acquire(p) - target) < 0)) { if (give_up(++it, 5)) break; __nanosleep(64); }
}

constexpr int G_ST = 32768, G_NST = 7, G_MB = G_ST * G_NST, GB_W = G_MB  , GB_FULL = G_MB + 32, GB_EMPTY = G_MB + 96, G_SMEM = G_MB + 160;

constexpr int C_WV = 0, C_WO = 65536, C_KVQ = 131072, KVQ_ST = 20480, C_QM = 192512, C_OT = 194560, C_MEM = 196608,
              C_KM = 204800, KM_BUF = 8192  , C_SX = 221184, C_S2 = 224256, C_MISC = 226304;
constexpr int MB_WQ = C_MISC, MB_WK = C_MISC + 8, MB_WV = C_MISC + 16, MB_WO = C_MISC + 24, MB_ML = C_MISC + 32  , MB_MR = C_MISC + 48  ,
              MB_S = C_MISC + 64, MB_V = C_MISC + 72, MB_KVQ = C_MISC + 80  ;
constexpr int TX_S = 3072, TX_V = 4096 + 2048 + 64;
constexpr int C_WE = C_MISC + 112;
constexpr int C_MX = C_MISC + 128;
constexpr int C_WM = C_MISC + 192;
constexpr int C_XE = C_MISC + 256;
constexpr int C_GT = C_MISC + 512;
constexpr int C_SU = C_MISC + 704;
constexpr int C_DBG = C_MISC + 768;
constexpr int C_SMEM = C_DBG;
#define STAMP(slot)
#define STAMP2(slot)
#define STAMP_NEXT

__device__ __forceinline__ int fresh(int v) { asm volatile("" : "+r"(v)); return v; }

struct Args {
  CUtensorMap tmq, tmk, tmv, tmo;
  CUtensorMap pw[3];
  CUtensorMap pb[4];
  const bf16* x; const bf16* mem0; const bf16* wo; const bf16* gate_w; bf16* out;
  uint32_t zero;
  uint16_t first[NGC + 2];
  uint32_t job[MAXJOBS];
};
constexpr int K_SMEM = C_SMEM > G_SMEM ? C_SMEM : G_SMEM;

__device__ __forceinline__ void load_a(uint32_t* a, const uint8_t* p0, const uint8_t* p1, int d = 64) {
  ldg128(a, p0); ldg128(a + 4, p1); ldg128(a + 8, p0 + d); ldg128(a + 12, p1 + d);
}
__device__ __forceinline__ void frag_a(uint32_t* u, const uint32_t* a, uint32_t z) {
#pragma unroll
  for (int i = 0; i < 16; i++) { u[i] = a[(i & 8) | ((i & 1) << 2) | (i & 2) | ((i >> 2) & 1)] ^ z; asm volatile("" : "+r"(u[i])); }
}
#define GSTAMP(i)
#define QSTAMP(it, k)

__global__ void __launch_bounds__(384, 1)
fused_kernel(const __grid_constant__ Args args) {
  extern __shared__ __align__(1024) uint8_t smem[];
  const int tid = threadIdx.x;
  int lane = tid & 31;
  asm volatile("" : "+r"(lane));
  const int warp = __shfl_sync(~0u, tid >> 5, 0);
  const int cta = blockIdx.x, h = (cta >> 1) & 31, j = cta & 1;
  const uint32_t sb = smem_u32(smem);

  if (tid == 0 && cta >= 64) {
    for (int i = 0; i < 4; i++) mbar_init(sb + GB_W + 8 * i, 1);
    for (int i = 0; i < G_NST; i++) { mbar_init(sb + GB_FULL + 8 * i, 1); mbar_init(sb + GB_EMPTY + 8 * i, 16); }
    asm volatile("fence.mbarrier_init.release.cluster;" ::: "memory");
    if (cta < 128)
      for (int i = 0; i < 4; i++) {
        mbar_expect_tx(sb + GB_W + 8 * i, 49152);
        for (int b = 0; b < 3; b++) tma5d(sb + b * 65536 + i * 16384, &args.pw[b], h * DH + j * 64, 4 * i, sb + GB_W + 8 * i);
      }
  }
  if (tid == 0 && cta < 64) {
    mbar_init(sb + MB_WQ, 1); mbar_init(sb + MB_WK, 1); mbar_init(sb + MB_WV, 1); mbar_init(sb + MB_WO, 1);
    mbar_init(sb + MB_ML, 4); mbar_init(sb + MB_ML + 8, 4); mbar_init(sb + MB_MR, 1); mbar_init(sb + MB_MR + 8, 1);
    mbar_init(sb + MB_S, 1); mbar_init(sb + MB_V, 1);
    for (int i = 0; i < 3; i++) mbar_init(sb + MB_KVQ + 8 * i, 1);
    asm volatile("fence.mbarrier_init.release.cluster;" ::: "memory");
    const int col = h * DH + j * 64;
    mbar_expect_tx(sb + MB_WQ, 65536); tma2d(sb + C_WO, &args.tmq, col, 0, sb + MB_WQ); tma2d(sb + C_WO + 32768, &args.tmq, col, 256, sb + MB_WQ);
    mbar_expect_tx(sb + MB_WK, 65536); tma2d(sb + C_KVQ, &args.tmk, col, 0, sb + MB_WK); tma2d(sb + C_KVQ + 32768, &args.tmk, col, 256, sb + MB_WK);
    mbar_expect_tx(sb + MB_WV, 65536); tma2d(sb + C_WV, &args.tmv, col, 0, sb + MB_WV); tma2d(sb + C_WV + 32768, &args.tmv, col, 256, sb + MB_WV);
    mbar_expect_tx(sb + MB_MR, 2048); mbar_expect_tx(sb + MB_MR + 8, 2048); mbar_expect_tx(sb + MB_S, TX_S); mbar_expect_tx(sb + MB_V, TX_V);
  }
  const uint32_t tag = ldv32(&g_done) / NCTA + 1;
  asm volatile("barrier.cluster.arrive.aligned; barrier.cluster.wait.aligned;" ::: "memory");
  uint8_t* const ring = reinterpret_cast<uint8_t*>((reinterpret_cast<uintptr_t>(g_ring) + RING_SLOT - 1) & ~(uintptr_t)(RING_SLOT - 1));
  auto issue_stage = [&](int seg) {
    const int stg = seg % 3;
    const uint8_t* src = g_qkv + (size_t)(seg * NH + h) * BLK_BYTES;
    const uint32_t mb = sb + MB_KVQ + 8 * stg, dst = sb + C_KVQ + stg * KVQ_ST;
    mbar_expect_tx(mb, KVQ_ST + 64);
    bulk_g2s(dst, src, 16384, mb);
    bulk_g2s(dst + 16384, src + 16384 + j * 4096, 4096, mb);
    bulk_g2s(sb + C_GT + stg * 64, g_gate + seg * SEGL + 16 * j, 64, mb);
  };

  if (cta >= 64 && warp < 8) {
    asm volatile("setmaxnreg.inc.sync.aligned.u32 232;");
    const int wg = warp >> 2, w = warp & 3, g = lane >> 2, t = lane & 3;
    const uint64_t dsc_hi = (uint64_t)((2048 >> 4) | (1u << 30)) << 32;
    uint32_t A[4][16], U[2][16];
    GSTAMP(0);
    if (cta < 128) {
      float acc[96];
      const uint8_t* p0 = reinterpret_cast<const uint8_t*>(args.x) + (size_t)(wg * 64 + w * 16 + g) * (DM * 2) + t * 16;
#pragma unroll
      for (int i = 0; i < 4; i++) load_a(A[i], p0 + i * 128, p0 + i * 128 + 8192);
      const uint64_t dsc = dsc_hi | (uint64_t)(((sb >> 4) & 0x3FFF) | ((65536 >> 4) << 16));
      uint8_t* dst = g_qkv + (size_t)((2 * wg + (w >> 1)) * NH + h) * BLK_BYTES + (w & 1) * 4096 + j * 1024 + g * 64 + ((t ^ (g >> 1)) << 4);
      unsigned* fl = g_fq + (2 * wg + (w >> 1)) * NH + h;
      if (wg == 1) bar_sync<1, 256>();
      for (int it = 0; it < 16; it++) {
        QSTAMP(it, 0);
#pragma unroll
        for (int kc = 0; kc < 8; kc++) {
          if (it == 0) mbar_wait(sb + GB_W + 8 * (kc >> 1), 0);
          uint32_t* a = U[kc & 1];
          frag_a(a, A[kc & 3], args.zero);
          wg_fence();
          wgmma_rs192(acc, a[0], a[1], a[2], a[3], dsc + kc * 512, kc != 0);
          wgmma_rs192(acc, a[4], a[5], a[6], a[7], dsc + kc * 512 + 64, 1);
          wgmma_rs192(acc, a[8], a[9], a[10], a[11], dsc + kc * 512 + 256, 1);
          wgmma_rs192(acc, a[12], a[13], a[14], a[15], dsc + kc * 512 + 320, 1);
          wg_commit();
          const uint8_t* pn = p0 + (kc < 4 ? (kc + 4) * 128 : 128 * DM * 2 + (kc - 4) * 128);
          if (kc < 4 || it < 15) load_a(A[kc & 3], pn, pn + 8192);
          if (kc == 0 && it > 0) { __syncwarp(); if (lane == 0) red_release(fl - 4 * NH); }
          if (kc == 0) { QSTAMP(it, 1); }
          if (kc == 4) { QSTAMP(it, 4); }
          if (kc == 3 && it == 0 && wg == 0) bar_arrive<1, 256>();
          wg_wait<1>();
        }
        wg_wait<0>();
        QSTAMP(it, 2);
#pragma unroll
        for (int b = 0; b < 6; b++) {
          const float* d = acc + 16 * b;
          uint8_t* q = dst + (b >> 1) * 8192 + (b & 1) * 512;
          *reinterpret_cast<uint4*>(q) = make_uint4(pack_bf16(d[0], d[1]), pack_bf16(d[4], d[5]), pack_bf16(d[8], d[9]), pack_bf16(d[12], d[13]));
          *reinterpret_cast<uint4*>(q + 2048) = make_uint4(pack_bf16(d[2], d[3]), pack_bf16(d[6], d[7]), pack_bf16(d[10], d[11]), pack_bf16(d[14], d[15]));
        }
        QSTAMP(it, 3);
        p0 += 128 * DM * 2; dst += (size_t)4 * NH * BLK_BYTES; fl += 4 * NH;
      }
      __syncwarp();
      if (lane == 0) red_release(fl - 4 * NH);
    }
    GSTAMP(1);
    const uint32_t ea = mapa(sb + GB_EMPTY, lane & 1);
    if (lane < 2 * G_NST) mbar_arrive_cluster(ea + 8 * (lane >> 1));
    const int gc = (cta - 64) >> 1;
    const int jn = args.first[gc + 1];
    int ji = args.first[gc];
    const uint64_t dsc = dsc_hi | (uint64_t)(((sb >> 4) & 0x3FFF) | ((8192 >> 4) << 16));
    uint32_t st = 0, ph = 0;
    bool loaded = false, gate_ok = false;
    const uint8_t *p0, *p1;
    int ad;
    auto set_a = [&](uint32_t job) {
      const int m16 = ((job >> 1) & 7) * 16 + j * 8 + warp;
      const bool fin = job & 1;
      p0 = fin ? g_a + (size_t)m16 * A_TILE + ((job >> 8) & 127) * 2048 + lane * 16
               : reinterpret_cast<const uint8_t*>(args.x) + (size_t)(m16 * 16 + g) * (DM * 2) + t * 16;
      p1 = p0 + (fin ? 512 : 8 * DM * 2);
      ad = fin ? 1024 : 64;
    };
    auto dep_ptr = [&](uint32_t job) { return (((job >> 8) & 127) < 64 ? g_fo : g_fh) + ((job >> 1) & 7) * 16 + j * 8 + warp; };
    auto dep_cnt = [&](uint32_t job) { return tag * (((job >> 8) & 127) < 64 ? 32u : 14u); };
    if (wg == 1) bar_sync<2, 256>();
    bool lead = wg == 0;
    float acc[128];
    for (; ji < jn; ji++) {
      const uint32_t job = args.job[ji];
      if (!loaded) {
        if (job & 1) wait_count(dep_ptr(job), dep_cnt(job));
        set_a(job);
        load_a(A[0], p0, p1, ad); load_a(A[1], p0 + 2 * ad, p1 + 2 * ad, ad);
      }
      QSTAMP(16 + ji - args.first[gc], 0);
      const uint32_t nxt = args.job[ji + 1];
      const uint32_t dep = ld_relaxed(dep_ptr(nxt));
      const int nk = (job >> 15) & 127;
      uint32_t pst = 0;
      for (int k = 0; k < nk; k += 2) {
#pragma unroll
        for (int u = 0; u < 2; u++) {
          uint32_t* a = U[u];
          mbar_wait(sb + GB_FULL + 8 * st, ph);
          frag_a(a, A[u], args.zero);
          const uint64_t d = dsc + st * (G_ST >> 4);
          wg_fence();
          wgmma_rs256(acc, a[0], a[1], a[2], a[3], d, u != 0 || k != 0);
          wgmma_rs256(acc, a[4], a[5], a[6], a[7], d + 64, 1);
          wgmma_rs256(acc, a[8], a[9], a[10], a[11], d + 256, 1);
          wgmma_rs256(acc, a[12], a[13], a[14], a[15], d + 320, 1);
          wg_commit();
          if (k + 2 < nk) load_a(A[u], p0 + (2 * u + 4) * ad, p1 + (2 * u + 4) * ad, ad);
          if (u == 0 && k == 2 && lead) { bar_arrive<2, 256>(); lead = false; }
          wg_wait<1>();
          if ((u != 0 || k != 0) && lane < 2) mbar_arrive_cluster(ea + 8 * pst);
          pst = st;
          if (++st == G_NST) { st = 0; ph ^= 1; }
        }
        p0 += 4 * ad; p1 += 4 * ad;
      }
      wg_wait<0>();
      QSTAMP(16 + ji - args.first[gc], 2);
      if (lane < 2) mbar_arrive_cluster(ea + 8 * pst);
      loaded = ji + 1 < jn && (!(nxt & 1) || (int)(dep - dep_cnt(nxt)) >= 0);
      if (loaded) {
        if (nxt & 1) fence_gpu();
        set_a(nxt);
        load_a(A[0], p0, p1, ad); load_a(A[1], p0 + 2 * ad, p1 + 2 * ad, ad);
      }
      QSTAMP(16 + ji - args.first[gc], 1);
      const int m16 = ((job >> 1) & 7) * 16 + j * 8 + warp, n = (job >> 4) & 15;
      const int row = m16 * 16 + g;
      if (!(job & 1)) {
        if (!gate_ok) {
          int it = 0;
          while (!__all_sync(~0u, ldv32(&g_pub[lane]) == tag && ldv32(&g_pub[lane + 32]) == tag)) { if (give_up(++it, 6)) break; }
          fence_gpu();
          gate_ok = true;
        }
        const float s0 = 1.0f - __ldcg(g_gate + row), s1 = 1.0f - __ldcg(g_gate + row + 8);
        uint8_t* q = g_a + (size_t)m16 * A_TILE + (HD / 32 + n * 4) * 1024 + lane * 16;
#pragma unroll
        for (int b = 0; b < 4; b++) {
          uint32_t lo[4], hi[4];
#pragma unroll
          for (int i = 0; i < 4; i++) {
            const float* ga = acc + 16 * b + 4 * i;
            float v[4];
#pragma unroll
            for (int e = 0; e < 4; e++) v[e] = __fdividef(ga[64 + e] * (e < 2 ? s0 : s1), 1.0f + ex2(ga[e] * -1.4426950408889634f));
            lo[i] = pack_bf16(v[0], v[1]); hi[i] = pack_bf16(v[2], v[3]);
          }
          *reinterpret_cast<uint4*>(q + 1024 * b) = make_uint4(lo[0], lo[1], lo[2], lo[3]);
          *reinterpret_cast<uint4*>(q + 1024 * b + 512) = make_uint4(hi[0], hi[1], hi[2], hi[3]);
        }
        QSTAMP(16 + ji - args.first[gc], 4);
        __syncwarp();
        if (lane == 0) red_release(g_fh + m16);
      } else {
        float* q = g_acc + (size_t)row * DM + n * 256 + 2 * t;
        unsigned* fc = g_fc + m16 * 2 + n;
        const uint32_t parts = job >> 23, base = (tag - 1) * parts;
        if (job & (1u << 22)) {
#pragma unroll
          for (int i = 0; i < 32; i++) {
            *reinterpret_cast<float2*>(q + 8 * i) = make_float2(acc[4 * i], acc[4 * i + 1]);
            *reinterpret_cast<float2*>(q + 8 * i + 8 * DM) = make_float2(acc[4 * i + 2], acc[4 * i + 3]);
          }
          __syncwarp();
          if (lane == 0) red_release(fc);
        } else {
          wait_count(fc, base + 1);
#pragma unroll
          for (int i = 0; i < 32; i++) {
            asm volatile("red.relaxed.gpu.global.add.v2.f32 [%0], {%1,%2};" :: "l"(q + 8 * i), "f"(acc[4 * i]), "f"(acc[4 * i + 1]) : "memory");
            asm volatile("red.relaxed.gpu.global.add.v2.f32 [%0], {%1,%2};" :: "l"(q + 8 * i + 8 * DM), "f"(acc[4 * i + 2]), "f"(acc[4 * i + 3]) : "memory");
          }
          __syncwarp();
          uint32_t tk = 0;
          if (lane == 0) asm volatile("atom.acq_rel.gpu.global.add.u32 %0, [%1], 1;" : "=r"(tk) : "l"(fc) : "memory");
          tk = __shfl_sync(~0u, tk, 0);
          if (tk == base + parts - 1) {
            const float4* s = reinterpret_cast<const float4*>(g_acc + (size_t)m16 * 16 * DM + n * 256) + 2 * lane;
            uint4* o = reinterpret_cast<uint4*>(args.out + (size_t)m16 * 16 * DM + n * 256) + lane;
#pragma unroll
            for (int r = 0; r < 32; r++) {
              const float4 v = __ldcg(s + (r >> 1) * (DM / 4) + (r & 1));
              acc[4 * r] = v.x; acc[4 * r + 1] = v.y; acc[4 * r + 2] = v.z; acc[4 * r + 3] = v.w;
            }
#pragma unroll
            for (int r = 0; r < 16; r++) {
              const float* a = acc + 8 * r;
              o[r * (DM / 8)] = make_uint4(pack_bf16(a[0], a[1]), pack_bf16(a[2], a[3]), pack_bf16(a[4], a[5]), pack_bf16(a[6], a[7]));
            }
          }
        }
      }
      GSTAMP(2 + ji - args.first[gc]);
      QSTAMP(16 + ji - args.first[gc], 3);
    }
    if (lead) bar_arrive<2, 256>();
    asm volatile("barrier.cluster.arrive.aligned; barrier.cluster.wait.aligned;" ::: "memory");
  } else if (cta >= 64) {
    asm volatile("setmaxnreg.dec.sync.aligned.u32 40;");
    if (warp == 8 && lane == 0) {
      const int gc = (cta - 64) >> 1;
      const int jn = args.first[gc + 1];
      uint32_t st = 0, ph = 0;
      for (int ji = args.first[gc]; ji < jn; ji++) {
        const uint32_t job = args.job[ji];
        const int n = (job >> 4) & 15, k0 = (job >> 8) & 127, nk = (job >> 15) & 127;
        const CUtensorMap* tm = &args.pb[(job & 1) ? (k0 < 64 ? 2 : 3) : j];
        const int col = (job & 1) ? n * 256 + j * 128 : n * 128;
        for (int k = 0; k < nk; k++) {
          mbar_wait_cluster(sb + GB_EMPTY + 8 * st, ph);
          const uint32_t mb = sb + GB_FULL + 8 * st, dst = sb + st * G_ST + j * 16384;
          mbar_expect_tx(mb, G_ST);
          tma5d_mc(dst, tm, col, 2 * ((k0 & 63) + k), mb);
          tma5d_mc(dst + 8192, tm, col + 64, 2 * ((k0 & 63) + k), mb);
          if (++st == G_NST) { st = 0; ph ^= 1; }
        }
      }
      atomicAdd(&g_done, 1u);
    }
    __syncwarp();
    asm volatile("barrier.cluster.arrive.aligned; barrier.cluster.wait.aligned;" ::: "memory");
  } else if (warp < 8) {
    asm volatile("setmaxnreg.inc.sync.aligned.u32 " FAT_REGS ";");
    const int gam = warp >> 2, w = warp & 3;
    uint32_t wq[16][4], wk[16][4], R[16][4];
    auto w_off = [&](int l, int i) {
      const uint32_t o = ((l & 7) + ((l >> 4) << 3)) * 128 + (((2 * w + ((l >> 3) & 1)) ^ (l & 7)) << 4) + gam * 16384 + (i & 1) * 2048;
      return o + (i < 8 ? j * 32768 + ((w ^ (i >> 1)) << 12) : (j ^ 1) * 32768 + (((i >> 1) - 4) << 12));
    };
    mbar_wait(sb + MB_WQ, 0);
#pragma unroll
    for (int i = 0; i < 16; i++) ldm4t(wq[i], sb + C_WO + w_off(lane, i));
    mbar_wait(sb + MB_WK, 0);
#pragma unroll
    for (int i = 0; i < 16; i++) ldm4t(wk[i], sb + C_KVQ + w_off(lane, i));
    bar_sync<10, 384>();
    mbar_wait(sb + MB_WV, 0);
    {
      uint32_t m = 0;
#pragma unroll
      for (int i = 0; i < 16; i++) {
        ldm4t(R[i], sb + C_WV + w_off(lane, i));
        m = absmax2(absmax2(m, absmax2(R[i][0], R[i][1])), absmax2(R[i][2], R[i][3]));
      }
      m = __reduce_max_sync(~0u, fold_absmax(m));
      if (lane == 0) sts32(sb + C_WM + warp * 4, m);
      bar_arrive<11, 384>();
    }
    const uint32_t peer_d = mapa(sb, j ^ 1) - sb, self_d = mapa(sb, j) - sb;
    const int delay = POLL_DELAY;
    uint32_t pk[4];
#pragma unroll
    for (int i = 0; i < 4; i++)
      pk[i] = __ldg(reinterpret_cast<const uint32_t*>(args.mem0 + (lane >> 2) * DM + j * 256 + warp * 32 + i * 8 + 2 * (lane & 3)));
    mbar_wait(sb + MB_WO, 0);
    int E = 0;
    uint32_t ma = sb + C_MEM + j * 4096 + gam * 2048 + (lane >> 3) * 512 + w * 128 + (lane & 7) * 16;
    for (int s = 0;; s++) {
      STAMP(0);
      st_async128(ma + peer_d, pk[0], pk[1], pk[2], pk[3], sb + MB_MR + gam * 8 + peer_d);
      sts128(ma, pk[0], pk[1], pk[2], pk[3]);
      __syncwarp();
      if (lane == 0) mbar_arrive(sb + MB_ML + gam * 8);
      float cq[4], ck[4], cv[4], cw[4];
      uint32_t b[8][4], Wo[16][4];
      mma16z(ck, wk[0][0], wk[0][1], wk[0][2], wk[0][3], pk[0], pk[1]);
      mma16z(cq, wq[0][0], wq[0][1], wq[0][2], wq[0][3], pk[0], pk[1]);
      mma16z(cv, R[0][0], R[0][1], R[0][2], R[0][3], pk[0], pk[1]);
      const uint32_t mx = __reduce_max_sync(~0u, fold_absmax(absmax2(absmax2(pk[0], pk[1]), absmax2(pk[2], pk[3]))));
      mma16(ck, wk[1][0], wk[1][1], wk[1][2], wk[1][3], pk[2], pk[3]);
      mma16(cq, wq[1][0], wq[1][1], wq[1][2], wq[1][3], pk[2], pk[3]);
      mma16(cv, R[1][0], R[1][1], R[1][2], R[1][3], pk[2], pk[3]);
      mbar_wait(sb + MB_ML + gam * 8, s & 1);
      STAMP(1);
      lds128r(b[1], ma ^ 128);
      lds128r(b[2], ma ^ 256);
      const uint32_t mr = (ma & ~384u) + (j ? -4096 : 4096);
#pragma unroll
      for (int i = 1; i < 8; i++) {
        mma16(ck, wk[2 * i][0], wk[2 * i][1], wk[2 * i][2], wk[2 * i][3], b[i][0], b[i][1]);
        mma16(cq, wq[2 * i][0], wq[2 * i][1], wq[2 * i][2], wq[2 * i][3], b[i][0], b[i][1]);
        if (i < NVQ) mma16(cv, R[2 * i][0], R[2 * i][1], R[2 * i][2], R[2 * i][3], b[i][0], b[i][1]);
        if (i == 1) lds128r(b[3], ma ^ 384);
        if (i == 3) { mbar_wait_cluster(sb + MB_MR + gam * 8, s & 1); lds128r(b[4], mr); lds128r(b[5], mr + 128); }
        if (i == 4 || i == 5) lds128r(b[i + 2], mr + (i - 2) * 128);
        mma16(ck, wk[2 * i + 1][0], wk[2 * i + 1][1], wk[2 * i + 1][2], wk[2 * i + 1][3], b[i][2], b[i][3]);
        mma16(cq, wq[2 * i + 1][0], wq[2 * i + 1][1], wq[2 * i + 1][2], wq[2 * i + 1][3], b[i][2], b[i][3]);
        if (i < NVQ) mma16(cv, R[2 * i + 1][0], R[2 * i + 1][1], R[2 * i + 1][2], R[2 * i + 1][3], b[i][2], b[i][3]);
        if (i == 2 && lane < 2) st_async32(sb + C_MX + (j * 8 + warp) * 4 + (lane ? peer_d : self_d), mx, sb + MB_V + (lane ? peer_d : self_d));
      }
      const float up = __uint_as_float((uint32_t)(127 + E) << 23);
      const int la = fresh(lane);
      const uint32_t km = sb + C_KM + (s & 1) * KM_BUF;
      const uint32_t k_lo = pack_bf16(ck[0] * up, ck[1] * up), k_hi = pack_bf16(ck[2] * up, ck[3] * up);
      {
        const int r = la & 7;
        const uint32_t o = (2 * (w >> 1) + (r >> 2)) * 512 + ((r ^ (4 * (w & 1) + 2 * ((la >> 3) & 1))) << 4);
        const uint32_t a = (la & 16) ? km + j * 2048 + gam * 256 + ((r >> 1) & 1) * 128 : sb + C_QM + gam * 128 + ((r >> 1) & 1) * 256;
        stm4(a + o, pack_bf16(cq[0] * up, cq[1] * up), pack_bf16(cq[2] * up, cq[3] * up), k_lo, k_hi);
      }
      bar_arrive<6, 384>();
      STAMP(2);
      mma16z(cw, R[2 * NVQ + 1][0], R[2 * NVQ + 1][1], R[2 * NVQ + 1][2], R[2 * NVQ + 1][3], b[NVQ][2], b[NVQ][3]);
      mma16(cv, R[2 * NVQ][0], R[2 * NVQ][1], R[2 * NVQ][2], R[2 * NVQ][3], b[NVQ][0], b[NVQ][1]);
#pragma unroll
      for (int i = NVQ + 1; i < 8; i++) {
        mma16(cw, R[2 * i + 1][0], R[2 * i + 1][1], R[2 * i + 1][2], R[2 * i + 1][3], b[i][2], b[i][3]);
        mma16(cv, R[2 * i][0], R[2 * i][1], R[2 * i][2], R[2 * i][3], b[i][0], b[i][1]);
      }
      {
        const int g = la >> 2;
        const uint32_t a = km + (4 * j + 2 * (w >> 1) + (g >> 2)) * 512 + gam * 256 + ((g >> 1) & 1) * 128 + ((g ^ (4 * (w & 1))) << 4) + (la & 3) * 4;
        const uint32_t mv = sb + MB_V;
        st_async32(a + peer_d, k_lo, mv + peer_d);
        st_async32((a ^ 32) + peer_d, k_hi, mv + peer_d);
        if (w == 0 && la == 0) mbar_expect_tx(sb + MB_MR + gam * 8, 2048);
        const uint32_t lo = pack_bf16((cv[0] + cw[0]) * up, (cv[1] + cw[1]) * up), hi = pack_bf16((cv[2] + cw[2]) * up, (cv[3] + cw[3]) * up);
        st_async32(a + 4096 + peer_d, lo, mv + peer_d);
        st_async32((a ^ 32) + 4096 + peer_d, hi, mv + peer_d);
        st_async32(a + 4096 + self_d, lo, mv + self_d);
        st_async32((a ^ 32) + 4096 + self_d, hi, mv + self_d);
      }
      STAMP(6);
      if (s == NSEG - 1) break;
      const uint32_t wo_a = sb + C_WO + (warp >> 1) * 16384 + ((la & 7) + ((la >> 4) << 3)) * 128 + ((((warp & 1) * 4 + ((la >> 3) & 1)) ^ (la & 7)) << 4);
#pragma unroll
      for (int u = 0; u < WO_EARLY; u++)
        ldm4t(Wo[u], ((wo_a ^ ((u & 1) << 5)) | (u >= WO_PAR ? Wo[u - WO_PAR][0] & args.zero : 0u)) + ((u >> 1) << 11));
      if (s == 0) bar_sync<12, 384>();
      mbar_wait_cluster(sb + MB_V, s & 1);
      E = max((int)(__reduce_max_sync(~0u, lds32(sb + C_MX + (la & 15) * 4)) >> 7) + E, (int)lds32(sb + C_XE + s * 4)) + (int)lds32(sb + C_WE);
      E = min(max(E, -100), 100);
      uint8_t* const rp = ring + (s & 7) * RING_SLOT + (j * 16 + warp * 2 + (la >> 4)) * 1024;
      uint8_t* rp16 = rp + ((la >> 3) & 1) * 256 + (la & 7) * 16;
      uint8_t* rp4 = rp + 128 + ((la >> 1) & 7) * 4;
      uint32_t ot_ld = sb + C_OT + (la ^ (((la >> 3) & 3) << 1)) * 16;
      uint32_t su_ld = sb + C_SU + (la & 3) * 8;
      asm volatile("" : "+l"(rp16), "+l"(rp4), "+r"(ot_ld), "+r"(su_ld));
      bar_sync<7, 384>();
      STAMP2(3);
#pragma unroll
      for (int i = 0; i < 4; i++) ldm4t(b[i], ot_ld + i * 512);
      const float2 su = lds64f(su_ld);
#pragma unroll
      for (int u = WO_EARLY; u < 16; u++) ldm4t(Wo[u], (wo_a ^ ((u & 1) << 5)) + ((u >> 1) << 11));
      mma16z(cq, Wo[0][0], Wo[0][1], Wo[0][2], Wo[0][3], b[0][0], b[0][1]);
      mma16z(ck, Wo[1][0], Wo[1][1], Wo[1][2], Wo[1][3], b[0][0], b[0][1]);
      mma16z(cv, Wo[2][0], Wo[2][1], Wo[2][2], Wo[2][3], b[0][2], b[0][3]);
      mma16z(cw, Wo[3][0], Wo[3][1], Wo[3][2], Wo[3][3], b[0][2], b[0][3]);
      const float dn = __uint_as_float((uint32_t)(127 - E) << 23);
      const float r0 = rcp(su.x) * dn, r1 = rcp(su.y) * dn;
#pragma unroll
      for (int k = 1; k < 4; k++) {
        mma16(cq, Wo[4 * k][0], Wo[4 * k][1], Wo[4 * k][2], Wo[4 * k][3], b[k][0], b[k][1]);
        mma16(ck, Wo[4 * k + 1][0], Wo[4 * k + 1][1], Wo[4 * k + 1][2], Wo[4 * k + 1][3], b[k][0], b[k][1]);
        mma16(cv, Wo[4 * k + 2][0], Wo[4 * k + 2][1], Wo[4 * k + 2][2], Wo[4 * k + 2][3], b[k][2], b[k][3]);
        mma16(cw, Wo[4 * k + 3][0], Wo[4 * k + 3][1], Wo[4 * k + 3][2], Wo[4 * k + 3][3], b[k][2], b[k][3]);
      }
      {
        const uint32_t u0 = movm(pack_f16((cq[0] + cv[0]) * r0, (cq[1] + cv[1]) * r1)), u1 = movm(pack_f16((cq[2] + cv[2]) * r0, (cq[3] + cv[3]) * r1));
        const uint32_t u2 = movm(pack_f16((ck[0] + cw[0]) * r0, (ck[1] + cw[1]) * r1)), u3 = movm(pack_f16((ck[2] + cw[2]) * r0, (ck[3] + cw[3]) * r1));
        asm volatile("red.relaxed.gpu.global.add.noftz.v4.f16x2 [%0], {%1,%2,%3,%4};"
                     :: "l"(rp16), "r"(u0), "r"(u1), "r"(u2), "r"(__byte_perm(u3, 0x3C00u, (la & 1) ? 0x5410 : 0x3210)) : "memory");
        if (la & 1) asm volatile("red.relaxed.gpu.global.add.noftz.f16x2 [%0], %1;" :: "l"(rp4), "r"(__byte_perm(u3, 0x3C00u, 0x5432)) : "memory");
      }
      bar_arrive<9, 384>();
      STAMP(4);
      const int lb = fresh(lane);
#pragma unroll
      for (int i = 0; i < WV_A; i++) ldm4t(R[i], sb + C_WV + w_off(lb, i));
      {
        float z = __uint_as_float(R[WV_A - 1][3] & 1u);
        for (int i = 0; i < delay; i++) asm volatile("fma.rn.f32 %0, %0, %0, %0; fma.rn.f32 %0, %0, %0, %0; fma.rn.f32 %0, %0, %0, %0; fma.rn.f32 %0, %0, %0, %0;" : "+f"(z));
        rp16 += __float_as_uint(z) >> 8;
      }
      STAMP(5);
      uint4 a0 = ldv128(rp16);
      uint32_t b0 = ldv32(rp4);
#pragma unroll
      for (int i = WV_A; i < 16; i++) ldm4t(R[i], sb + C_WV + w_off(lb, i));
      const uint32_t ev = (lb & 1) - 1u, sel = (lb & 1) ? 0x5410 : 0x3210;
      int it = 0;
      while (!__all_sync(~0u, (((a0.w | ev) & b0) >> 16) == 0x5000u)) {
        if (give_up(++it, 3)) break;
        a0 = ldv128(rp16); b0 = ldv32(rp4);
      }
      pk[0] = f16_to_bf16(a0.x); pk[1] = f16_to_bf16(a0.y); pk[2] = f16_to_bf16(a0.z); pk[3] = f16_to_bf16(__byte_perm(a0.w, b0, sel));
      STAMP_NEXT;
    }
  } else {
    asm volatile("setmaxnreg.dec.sync.aligned.u32 " AUX_REGS ";");
    const int w = warp - 8, at = tid - 256;
    {
      if (at < 80) *reinterpret_cast<uint4*>(ring + (at / 10) * RING_SLOT + (cta >> 1) * 1024 + j * 256 + (at % 10) * 16) = make_uint4(0, 0, 0, 0);
      uint32_t mx = 0, mo = 0;
      const uint4 gw0 = __ldg(reinterpret_cast<const uint4*>(args.gate_w) + lane), gw1 = __ldg(reinterpret_cast<const uint4*>(args.gate_w) + 32 + lane);
#pragma unroll 2
      for (int r = 0; r < 8; r++) {
        const int tok = cta * SEGL + w * 8 + r;
        const uint4* xr = reinterpret_cast<const uint4*>(args.x + (size_t)tok * DM);
        const uint4 a = __ldg(xr + lane), b = __ldg(xr + 32 + lane);
        float acc = bf_lo(a.x) * bf_lo(gw0.x) + bf_hi(a.x) * bf_hi(gw0.x) + bf_lo(a.y) * bf_lo(gw0.y) + bf_hi(a.y) * bf_hi(gw0.y) +
                    bf_lo(a.z) * bf_lo(gw0.z) + bf_hi(a.z) * bf_hi(gw0.z) + bf_lo(a.w) * bf_lo(gw0.w) + bf_hi(a.w) * bf_hi(gw0.w) +
                    bf_lo(b.x) * bf_lo(gw1.x) + bf_hi(b.x) * bf_hi(gw1.x) + bf_lo(b.y) * bf_lo(gw1.y) + bf_hi(b.y) * bf_hi(gw1.y) +
                    bf_lo(b.z) * bf_lo(gw1.z) + bf_hi(b.z) * bf_hi(gw1.z) + bf_lo(b.w) * bf_lo(gw1.w) + bf_hi(b.w) * bf_hi(gw1.w);
        mx = absmax2(absmax2(mx, absmax2(absmax2(a.x, a.y), absmax2(a.z, a.w))), absmax2(absmax2(b.x, b.y), absmax2(b.z, b.w)));
#pragma unroll
        for (int o = 16; o; o >>= 1) acc += __shfl_xor_sync(~0u, acc, o);
        if (lane == 0) g_gate[tok] = __fdividef(1.0f, 1.0f + __expf(-acc));
      }
      const uint4* wr = reinterpret_cast<const uint4*>(args.wo + (size_t)(h * DH + w * 32) * DM + j * 256) + lane;
#pragma unroll 8
      for (int r = 0; r < 32; r++) {
        const uint4 a = __ldg(wr + r * (DM / 8));
        mo = absmax2(mo, absmax2(absmax2(a.x, a.y), absmax2(a.z, a.w)));
      }
      mx = __reduce_max_sync(~0u, fold_absmax(mx));
      mo = __reduce_max_sync(~0u, fold_absmax(mo));
      if (lane == 0) { sts32(sb + C_WM + 32 + w * 4, mx); sts32(sb + C_WM + 48 + w * 4, mo); }
      __threadfence();
    }
    bar_sync<10, 384>();
    if (at == 0) {
      mbar_expect_tx(sb + MB_WO, 65536);
      for (int i = 0; i < 4; i++) tma2d(sb + C_WO + i * 16384, &args.tmo, j * 256 + i * 64, h * DH, sb + MB_WO);
    }
    bar_sync<11, 384>();
    {
      if (at == 0) {
        const uint4 a = lds128(sb + C_WM), b = lds128(sb + C_WM + 16), c = lds128(sb + C_WM + 32), d = lds128(sb + C_WM + 48);
        uint4 r;
        r.x = tag;
        r.y = max(max(c.x, c.y), max(c.z, c.w)) >> 7;
        r.z = max(max(max(a.x, a.y), max(a.z, a.w)), max(max(b.x, b.y), max(b.z, b.w))) >> 7;
        r.w = max(max(d.x, d.y), max(d.z, d.w)) >> 7;
        asm volatile("st.volatile.global.v4.u32 [%0], {%1,%2,%3,%4};" :: "l"(&g_pub[cta]), "r"(r.x), "r"(r.y), "r"(r.z), "r"(r.w) : "memory");
      }
      if (w == 3) {
        uint4 r0, r1;
        int it = 0;
        while (true) {
          r0 = ldv128(&g_pub[lane]); r1 = ldv128(&g_pub[lane + 32]);
          if (__all_sync(~0u, r0.x == tag && r1.x == tag)) break;
          if (give_up(++it, 4)) break;
        }
        __threadfence();
        sts32(sb + C_XE + lane * 4, r0.y); sts32(sb + C_XE + 128 + lane * 4, r1.y);
        sts32(sb + C_WE, __reduce_max_sync(~0u, max(r0.z, r1.z)) + __reduce_max_sync(~0u, max(r0.w, r1.w)) - 3 * 126 + 21 - 14);
        for (int i = 0; i < 2; i++) {
          wait_count(g_fq + i * NH + h, tag * 4);
          asm volatile("fence.proxy.async.global;" ::: "memory");
          if (lane == 0) issue_stage(i);
        }
      }
      bar_arrive<12, 384>();
    }
    const uint32_t peer_d = mapa(sb, j ^ 1) - sb, self_d = mapa(sb, j) - sb;
    const float SC = 0.08838834764831845f * 1.4426950408889634f;
    int st = 0, stp = 0;
    for (int s = 0; s < NSEG; s++) {
      const uint32_t kv = sb + C_KVQ + st * KVQ_ST;
      const uint32_t km = sb + C_KM + (s & 1) * KM_BUF;
      uint32_t kb[4][4], va[4][4], vm[2][4];
      uint32_t fq = 0;
      if (w == 3) fq = ld_relaxed(g_fq + min(s + 2, NSEG - 1) * NH + h);
      {
        const int l = fresh(lane), r = l & 7;
        const uint32_t k_l = kv + r * 64 + (((l >> 3) ^ (r >> 1)) << 4);
        const uint32_t q_l = kv + 16384 + ((l >> 3) & 1) * 2048 + r * 64 + (((l >> 4) ^ (r >> 1)) << 4);
        mbar_wait(sb + MB_KVQ + 8 * st, stp);
        float s0[4], s1[4];
#pragma unroll
        for (int i = 0; i < 4; i++) {
          uint32_t a[4], c[4];
          ldm4(kb[0], k_l + w * 2048 + i * 512);
          ldm4(a, q_l + i * 512);
          ldm4(c, (q_l ^ 32) + i * 512);
          if (i == 0) { mma16z(s0, a[0], a[1], a[2], a[3], kb[0][0], kb[0][1]); mma16z(s1, c[0], c[1], c[2], c[3], kb[0][2], kb[0][3]); }
          else { mma16(s0, a[0], a[1], a[2], a[3], kb[0][0], kb[0][1]); mma16(s1, c[0], c[1], c[2], c[3], kb[0][2], kb[0][3]); }
        }
        const float NEG = -1.0e9f * 1.4426950408889634f;
        const int d = 16 * j + (l >> 2) - 2 * (l & 3) - 8 * w;
        asm volatile("st.shared.v4.f32 [%0], {%1,%2,%3,%4};" :: "r"(sb + C_S2 + w * 512 + l * 16), "f"(d >= 0 ? (s0[0] + s1[0]) * SC : NEG),
                     "f"(d >= 1 ? (s0[1] + s1[1]) * SC : NEG), "f"(d >= -8 ? (s0[2] + s1[2]) * SC : NEG), "f"(d >= -7 ? (s0[3] + s1[3]) * SC : NEG) : "memory");
#pragma unroll
        for (int i = 0; i < 4; i++) ldm4(kb[i], k_l + (w & 1) * 4096 + (i >> 1) * 2048 + j * 1024 + (i & 1) * 512);
      }
      auto load_v = [&]() {
        const int l = fresh(lane), r = l & 7;
        const uint32_t v_l = kv + 8192 + (l >> 4) * 2048 + w * 512 + r * 64 + ((((l >> 3) & 1) ^ (r >> 1)) << 4);
        ldm4t(va[0], v_l); ldm4t(va[1], v_l + 4096); ldm4t(va[2], v_l ^ 32); ldm4t(va[3], (v_l ^ 32) + 4096);
      };
      auto km_lane = [&](int l) { return (uint32_t)((l >> 3) * 128 + (((l & 7) ^ ((l >> 2) & 2)) << 4)); };
      if (s < NSEG - 1) {
        const int lq = fresh(lane);
        uint32_t q_a = sb + C_QM + (lq >> 3) * 128 + (((lq & 7) ^ ((lq >> 3) & 2)) << 4);
        uint32_t k_a = km + km_lane(lq);
        uint32_t sx = sb + C_SX + lq * 16;
        asm volatile("" : "+r"(q_a), "+r"(k_a), "+r"(sx));
        STAMP(13);
        bar_sync<6, 384>();
        STAMP2(8);
        if (w < 2) {
          uint32_t q[4][4];
          float s0[4], s1[4], s2[4], s3[4];
#pragma unroll
          for (int i = 0; i < 4; i++) ldm4t(q[i], (q_a ^ ((i & 1) << 6)) + i * 512);
          mma16z(s0, q[0][0], q[0][1], q[0][2], q[0][3], kb[0][0], kb[0][1]);
          mma16z(s2, q[0][0], q[0][1], q[0][2], q[0][3], kb[2][0], kb[2][1]);
          mma16z(s1, q[1][0], q[1][1], q[1][2], q[1][3], kb[0][2], kb[0][3]);
          mma16z(s3, q[1][0], q[1][1], q[1][2], q[1][3], kb[2][2], kb[2][3]);
          mma16(s0, q[2][0], q[2][1], q[2][2], q[2][3], kb[1][0], kb[1][1]);
          mma16(s2, q[2][0], q[2][1], q[2][2], q[2][3], kb[3][0], kb[3][1]);
          mma16(s1, q[3][0], q[3][1], q[3][2], q[3][3], kb[1][2], kb[1][3]);
          mma16(s3, q[3][0], q[3][1], q[3][2], q[3][3], kb[3][2], kb[3][3]);
          const uint32_t x0 = __float_as_uint((s0[0] + s0[2]) + (s1[0] + s1[2])), x1 = __float_as_uint((s0[1] + s0[3]) + (s1[1] + s1[3]));
          const uint32_t x2 = __float_as_uint((s2[0] + s2[2]) + (s3[0] + s3[2])), x3 = __float_as_uint((s2[1] + s2[3]) + (s3[1] + s3[3]));
          st_async128(sx + 1536 + w * 512 + peer_d, x0, x1, x2, x3, sb + MB_S + peer_d);
          st_async128(sx + w * 512 + self_d, x0, x1, x2, x3, sb + MB_S + self_d);
        } else {
          uint32_t q[2][4];
          float s0[4], s1[4];
          ldm4t(q[0], q_a + (w & 1) * 1024); ldm4t(kb[0], k_a + j * 2048 + (w & 1) * 1024);
          ldm4t(q[1], (q_a ^ 64) + (w & 1) * 1024 + 512); ldm4t(kb[1], (k_a ^ 64) + j * 2048 + (w & 1) * 1024 + 512);
          mma16z(s0, q[0][0], q[0][1], q[0][2], q[0][3], kb[0][0], kb[0][1]);
          mma16z(s1, q[0][0], q[0][1], q[0][2], q[0][3], kb[0][2], kb[0][3]);
          mma16(s0, q[1][0], q[1][1], q[1][2], q[1][3], kb[1][0], kb[1][1]);
          mma16(s1, q[1][0], q[1][1], q[1][2], q[1][3], kb[1][2], kb[1][3]);
          const uint32_t x0 = __float_as_uint((s0[0] + s0[2]) + (s1[0] + s1[2])), x1 = __float_as_uint((s0[1] + s0[3]) + (s1[1] + s1[3]));
          st_async64(sx + 2560 + (w & 1) * 8 + peer_d, x0, x1, sb + MB_S + peer_d);
          st_async64(sx + 1024 + (w & 1) * 8 + self_d, x0, x1, sb + MB_S + self_d);
        }
        STAMP(14);
        load_v();
        const int lc = fresh(lane);
        uint32_t ot_st = sb + C_OT + (32 * w + 8 * ((lc & 7) >> 1) + ((2 * (lc >> 3)) ^ (lc & 6)) + (lc & 1)) * 16;
        asm volatile("" : "+r"(ot_st));
        mbar_wait_cluster(sb + MB_S, s & 1);
        STAMP(9);
        const float4 u0 = lds128f(sx), u3 = lds128f(sx + 1536), u1 = lds128f(sx + 512), u4 = lds128f(sx + 2048), u2 = lds128f(sx + 1024), u5 = lds128f(sx + 2560);
        mbar_wait_cluster(sb + MB_V, s & 1);
        ldm4(vm[0], k_a + 4096 + w * 1024); ldm4(vm[1], (k_a ^ 64) + 4096 + w * 1024 + 512);
        const float sv[10] = {u0.x + u3.x, u0.y + u3.y, u0.z + u3.z, u0.w + u3.w, u1.x + u4.x, u1.y + u4.y, u1.z + u4.z, u1.w + u4.w,
                              (u2.x + u2.z) + (u5.x + u5.z), (u2.y + u2.w) + (u5.y + u5.w)};
        float m = fmaxf(fmaxf(fmaxf(sv[0], sv[1]), fmaxf(sv[2], sv[3])), fmaxf(fmaxf(sv[4], sv[5]), fmaxf(sv[6], sv[7])));
        m = fmaxf(m, fmaxf(sv[8], sv[9]));
        m = fmaxf(fmaxf(m, __shfl_xor_sync(~0u, m, 1)), fmaxf(__shfl_xor_sync(~0u, m, 2), __shfl_xor_sync(~0u, m, 3)));
        m *= -SC;
        uint32_t p[5];
#pragma unroll
        for (int i = 0; i < 5; i++) p[i] = pack_bf16(ex2(fmaf(sv[2 * i], SC, m)), ex2(fmaf(sv[2 * i + 1], SC, m)));
        float o0[4], o1[4], su[4];
        const uint32_t ONE = 0x3F803F80u;
        mma16z(o0, va[0][0], va[0][1], va[0][2], va[0][3], p[0], p[1]);
        mma16z(o1, va[2][0], va[2][1], va[2][2], va[2][3], p[0], p[1]);
        mma16z(su, ONE, ONE, ONE, ONE, p[0], p[1]);
        mma16(o0, va[1][0], va[1][1], va[1][2], va[1][3], p[2], p[3]);
        mma16(o1, va[3][0], va[3][1], va[3][2], va[3][3], p[2], p[3]);
        mma16(su, ONE, ONE, ONE, ONE, p[2], p[3]);
        mma16(o0, vm[0][0], vm[0][1], vm[0][2], vm[0][3], p[4], p[4]);
        mma16(o1, vm[1][0], vm[1][1], vm[1][2], vm[1][3], p[4], p[4]);
        mma8(su, ONE, ONE, p[4]);
        stm4(ot_st, pack_bf16(o0[0], o0[1]), pack_bf16(o0[2], o0[3]), pack_bf16(o1[0], o1[1]), pack_bf16(o1[2], o1[3]));
        if (lc == w) sts64f(sb + C_SU + w * 8, su[0], su[1]);
        bar_arrive<7, 384>();
        STAMP(10);
        if (w == 0 && lc == 0) { mbar_expect_tx(sb + MB_S, TX_S); mbar_expect_tx(sb + MB_V, TX_V); }
      } else {
        load_v();
        bar_sync<6, 384>();
        mbar_wait_cluster(sb + MB_V, s & 1);
      }
      if (w == 3) {
        if (lane == 0 && s > 0) {
          asm volatile("cp.async.bulk.wait_group 0;" ::: "memory");
          FLAG_O(g_fo + 2 * (s - 1) + j);
        }
        if (s + 2 < NSEG) {
          if ((int)(fq - tag * 4) < 0) wait_count(g_fq + (s + 2) * NH + h, tag * 4);
          asm volatile("fence.proxy.async.global;" ::: "memory");
          if (lane == 0) issue_stage(s + 2);
        }
        __syncwarp();
      }
      if (w == 1 && s >= 2 && lane < 10)
        *reinterpret_cast<uint4*>(ring + ((s - 2) & 7) * RING_SLOT + (cta >> 1) * 1024 + j * 256 + lane * 16) = make_uint4(0, 0, 0, 0);
      if (s < NSEG - 1) bar_sync<9, 384>();
      STAMP2(11);
      {
        const int l = fresh(lane), g = l >> 2, r = l & 7;
        const uint32_t q_l = kv + 16384 + ((l >> 3) & 1) * 2048 + r * 64 + (((l >> 4) ^ (r >> 1)) << 4);
        const uint32_t k_a = km + km_lane(l);
        float sc[5][4], s1[4];
#pragma unroll
        for (int i = 0; i < 8; i++) {
          uint32_t kk[4], a[4];
          ldm4t(kk, (k_a ^ ((i & 1) << 6)) + i * 512);
          ldm4(a, (q_l ^ ((i & 1) << 5)) + (i >> 1) * 512);
          if (i == 0) { mma16z(sc[4], a[0], a[1], a[2], a[3], kk[0], kk[1]); mma16z(s1, a[0], a[1], a[2], a[3], kk[2], kk[3]); }
          else { mma16(sc[4], a[0], a[1], a[2], a[3], kk[0], kk[1]); mma16(s1, a[0], a[1], a[2], a[3], kk[2], kk[3]); }
        }
#pragma unroll
        for (int i = 0; i < 4; i++) {
          const uint4 u = lds128(sb + C_S2 + i * 512 + l * 16);
          sc[i][0] = __uint_as_float(u.x); sc[i][1] = __uint_as_float(u.y); sc[i][2] = __uint_as_float(u.z); sc[i][3] = __uint_as_float(u.w);
          sc[4][i] = (sc[4][i] + s1[i]) * SC;
        }
        float m0 = -INFINITY, m1 = -INFINITY;
#pragma unroll
        for (int i = 0; i < 5; i++) {
          m0 = fmaxf(m0, fmaxf(sc[i][0], sc[i][1]));
          m1 = fmaxf(m1, fmaxf(sc[i][2], sc[i][3]));
        }
        m0 = fmaxf(m0, __shfl_xor_sync(~0u, m0, 1)); m0 = fmaxf(m0, __shfl_xor_sync(~0u, m0, 2));
        m1 = fmaxf(m1, __shfl_xor_sync(~0u, m1, 1)); m1 = fmaxf(m1, __shfl_xor_sync(~0u, m1, 2));
        float s0 = 0.f, s2 = 0.f;
        uint32_t p[5][2];
#pragma unroll
        for (int i = 0; i < 5; i++) {
          const float e0 = ex2(sc[i][0] - m0), e1 = ex2(sc[i][1] - m0), e2 = ex2(sc[i][2] - m1), e3 = ex2(sc[i][3] - m1);
          s0 += e0 + e1; s2 += e2 + e3;
          p[i][0] = pack_bf16(e0, e1); p[i][1] = pack_bf16(e2, e3);
        }
        ldm4(vm[0], k_a + 4096 + w * 1024); ldm4(vm[1], (k_a ^ 64) + 4096 + w * 1024 + 512);
        s0 += __shfl_xor_sync(~0u, s0, 1); s0 += __shfl_xor_sync(~0u, s0, 2);
        s2 += __shfl_xor_sync(~0u, s2, 1); s2 += __shfl_xor_sync(~0u, s2, 2);
        const float r0 = rcp(s0) * __uint_as_float(lds32(sb + C_GT + st * 64 + g * 4));
        const float r1 = rcp(s2) * __uint_as_float(lds32(sb + C_GT + st * 64 + 32 + g * 4));
        uint32_t lo[4], hi[4];
#pragma unroll
        for (int i = 0; i < 4; i++) {
          float o[4];
          mma16z(o, p[0][0], p[0][1], p[1][0], p[1][1], va[i & 2][i & 1], va[i & 2][(i & 1) + 2]);
          mma16(o, p[2][0], p[2][1], p[3][0], p[3][1], va[(i & 2) + 1][i & 1], va[(i & 2) + 1][(i & 1) + 2]);
          mma16(o, p[4][0], p[4][1], p[4][0], p[4][1], vm[i >> 1][i & 1], vm[i >> 1][(i & 1) + 2]);
          lo[i] = pack_bf16(o[0] * r0, o[1] * r0); hi[i] = pack_bf16(o[2] * r1, o[3] * r1);
        }
        sts128(kv + w * 1024 + l * 16, lo[0], lo[1], lo[2], lo[3]);
        sts128(kv + w * 1024 + 512 + l * 16, hi[0], hi[1], hi[2], hi[3]);
        asm volatile("fence.proxy.async.shared::cta;" ::: "memory");
      }
      bar_sync<8, 128>();
      if (w == 3 && lane == 0) {
        asm volatile("cp.async.bulk.global.shared::cta.bulk_group [%0], [%1], 4096;" :: "l"(g_a + (size_t)(2 * s + j) * A_TILE + h * 4096), "r"(kv) : "memory");
        asm volatile("cp.async.bulk.commit_group;" ::: "memory");
      }
      STAMP2(12);
      STAMP_NEXT;
      if (++st == 3) { st = 0; stp ^= 1; }
    }
    if (w == 3 && lane == 0) {
      asm volatile("cp.async.bulk.wait_group 0;" ::: "memory");
      FLAG_O(g_fo + 2 * (NSEG - 1) + j);
    }
    if (w == 0 && lane == 0) atomicAdd(&g_done, 1u);
  }
}

typedef CUresult (*EncodeFn)(CUtensorMap*, CUtensorMapDataType, cuuint32_t, void*, const cuuint64_t*, const cuuint64_t*, const cuuint32_t*,
                             const cuuint32_t*, CUtensorMapInterleave, CUtensorMapSwizzle, CUtensorMapL2promotion, CUtensorMapFloatOOBfill);
static void make_map(EncodeFn enc, CUtensorMap* tm, const void* base, uint64_t cols, uint64_t rows, uint32_t bc, uint32_t br) {
  cuuint64_t dims[2] = {cols, rows};
  cuuint64_t strides[1] = {cols * 2};
  cuuint32_t box[2] = {bc, br}, es[2] = {1, 1};
  enc(tm, CU_TENSOR_MAP_DATA_TYPE_BFLOAT16, 2, const_cast<void*>(base), dims, strides, box, es, CU_TENSOR_MAP_INTERLEAVE_NONE,
      CU_TENSOR_MAP_SWIZZLE_128B, CU_TENSOR_MAP_L2_PROMOTION_L2_256B, CU_TENSOR_MAP_FLOAT_OOB_FILL_NONE);
}

static int make_map5(EncodeFn enc, CUtensorMap* tm, const void* base, uint64_t cols, uint64_t rows, uint32_t groups, bool regroup) {
  const uint64_t rb = cols * 2;
  cuuint64_t dims[5] = {cols, 2, 4, 4, rows / 32};
  cuuint64_t strides[4] = {rb, (regroup ? 8 : 2) * rb, (regroup ? 2 : 8) * rb, 32 * rb};
  cuuint32_t box[5] = {64, 2, 4, 4, groups}, es[5] = {1, 1, 1, 1, 1};
  return (int)enc(tm, CU_TENSOR_MAP_DATA_TYPE_BFLOAT16, 5, const_cast<void*>(base), dims, strides, box, es, CU_TENSOR_MAP_INTERLEAVE_NONE,
                  CU_TENSOR_MAP_SWIZZLE_128B, CU_TENSOR_MAP_L2_PROMOTION_L2_256B, CU_TENSOR_MAP_FLOAT_OOB_FILL_NONE);
}

#define EST_STEP 4300.0
static void build_schedule(Args& a) {
  struct J { uint32_t code; int kind, p, n; double dur; bool done; };
  static J jobs[MAXJOBS];
  int nj = 0;
  const double KS = 1100.0, T0 = 12000.0, TQ = 115000.0;
  const int split[8] = {2, 2, 2, 2, 2, 2, 4, 16};
  for (int p = 0; p < 8; p++) for (int n = 0; n < 14; n++) jobs[nj++] = J{(uint32_t)(p << 1 | n << 4 | 8 << 15), 0, p, n, 8 * KS + 400, false};
  for (int p = 0; p < 8; p++) for (int n = 0; n < 2; n++)
    jobs[nj++] = J{(uint32_t)(1 | p << 1 | n << 4 | 64 << 8 | 28 << 15 | 1 << 22 | (split[p] + 1) << 23), 1, p, n, 28 * KS + 600, false};
  for (int p = 0; p < 8; p++) for (int q = 0; q < split[p]; q++) for (int n = 0; n < 2; n++) {
    const int nk = 64 / split[p];
    jobs[nj++] = J{(uint32_t)(1 | p << 1 | n << 4 | (q * nk) << 8 | nk << 15 | (split[p] + 1) << 23), 2, p, n, nk * KS + 1000, false};
  }
  double avail[NGC], hready[8] = {}, sready[16];
  int hleft[8]; bool sset[16] = {};
  static uint32_t lists[NGC][MAXJOBS]; int cnt[NGC] = {};
  for (int p = 0; p < 8; p++) hleft[p] = 14;
  for (int c = 0; c < NGC; c++) avail[c] = c < 32 ? TQ : 3000.0;
  for (int done = 0; done < nj; done++) {
    int c = 0;
    for (int i = 1; i < NGC; i++) if (avail[i] < avail[c]) c = i;
    int best = -1; double bt = 1e30;
    for (int i = 0; i < nj; i++) {
      J& q = jobs[i];
      if (q.done) continue;
      double r = 0;
      if (q.kind == 1) { if (hleft[q.p]) continue; r = hready[q.p]; }
      if (q.kind == 2) {
        if (!sset[q.p * 2 + q.n]) continue;
        r = T0 + (8 * q.p + 9) * EST_STEP;
        if (sready[q.p * 2 + q.n] - q.dur > r) r = sready[q.p * 2 + q.n] - q.dur;
      }
      if (r < avail[c]) r = avail[c];
      if (r < bt) { bt = r; best = i; }
    }
    J& q = jobs[best];
    q.done = true;
    avail[c] = bt + q.dur;
    lists[c][cnt[c]++] = q.code;
    if (q.kind == 0) { hleft[q.p]--; if (avail[c] > hready[q.p]) hready[q.p] = avail[c]; }
    if (q.kind == 1) { sset[q.p * 2 + q.n] = true; sready[q.p * 2 + q.n] = avail[c]; }
  }
  int o = 0;
  for (int c = 0; c < NGC; c++) { a.first[c] = (uint16_t)o; for (int i = 0; i < cnt[c]; i++) a.job[o++] = lists[c][i]; }
  a.first[NGC] = (uint16_t)o; a.first[NGC + 1] = 0; a.zero = 0;
  for (; o < MAXJOBS; o++) a.job[o] = 0;
}

extern "C" void kernel_launch(void* const* d_in, const int* in_sizes, int n_in, void* d_out, int out_size) {
  (void)in_sizes; (void)n_in; (void)out_size;
  const bf16 *wq = (const bf16*)d_in[2], *wk = (const bf16*)d_in[3], *wv = (const bf16*)d_in[4], *wo = (const bf16*)d_in[5],
             *wg = (const bf16*)d_in[8], *wu = (const bf16*)d_in[9], *wd = (const bf16*)d_in[10];
  static EncodeFn enc = nullptr;
  static Args a;
  if (!enc) {
    void* fn = nullptr; cudaDriverEntryPointQueryResult qr;
    cudaGetDriverEntryPoint("cuTensorMapEncodeTiled", &fn, cudaEnableDefault, &qr);
    enc = (EncodeFn)fn;
    cudaFuncSetAttribute(fused_kernel, cudaFuncAttributeMaxDynamicSharedMemorySize, K_SMEM);
    build_schedule(a);
  }
  make_map(enc, &a.tmq, wq, HD, DM, 64, 256); make_map(enc, &a.tmk, wk, HD, DM, 64, 256); make_map(enc, &a.tmv, wv, HD, DM, 64, 256);
  make_map(enc, &a.tmo, wo, DM, HD, 64, 128);
  int rc = make_map5(enc, &a.pw[0], wk, HD, DM, 4, true) | make_map5(enc, &a.pw[1], wv, HD, DM, 4, true) | make_map5(enc, &a.pw[2], wq, HD, DM, 4, true) |
           make_map5(enc, &a.pb[0], wg, FF, DM, 2, true) | make_map5(enc, &a.pb[1], wu, FF, DM, 2, true) |
           make_map5(enc, &a.pb[2], wo, DM, HD, 2, true) | make_map5(enc, &a.pb[3], wd, DM, FF, 2, false);
  if (rc) return;
  a.x = (const bf16*)d_in[0]; a.mem0 = (const bf16*)d_in[1]; a.wo = wo; a.gate_w = (const bf16*)d_in[11]; a.out = (bf16*)d_out;
  cudaLaunchConfig_t cfg = {};
  cfg.gridDim = dim3(NCTA); cfg.blockDim = dim3(384); cfg.dynamicSmemBytes = K_SMEM; cfg.stream = cudaStreamPerThread;
  cudaLaunchAttribute at[1];
  at[0].id = cudaLaunchAttributeClusterDimension; at[0].val.clusterDim.x = 2; at[0].val.clusterDim.y = 1; at[0].val.clusterDim.z = 1;
  cfg.attrs = at; cfg.numAttrs = 1;
  cudaLaunchKernelEx(&cfg, fused_kernel, a);
}
```

```cpp
#include <cuda_runtime.h>
#include <cuda_bf16.h>
#include <cuda_fp16.h>
#include <cuda.h>
#include <stdint.h>

typedef __nv_bfloat16 bf16;
#define FAT_REGS "216"
#define AUX_REGS "72"
#ifndef NVQ
#define NVQ 4
#endif
#define WO_EARLY 12
#define WO_PAR 2
#define WV_A 10
#define FLAG_O red_relaxed
#define POLL_DELAY 2

constexpr int SEQ = 2048, DM = 512, NH = 32, DH = 128, SEGL = 32, NSEG = 64, FF = 1792;
constexpr int HD = NH * DH;
constexpr int KA = HD + FF;
constexpr int NCTA = 132, NGC = 34, MAXJOBS = 320;
constexpr int BLK_BYTES = 24576;
constexpr int RING_SLOT = 32768;
constexpr int A_TILE = KA / 32 * 1024;
constexpr int SPIN_LIMIT = 1 << 20;

__device__ __align__(1024) uint8_t g_qkv[(size_t)NSEG * NH * BLK_BYTES];
__device__ __align__(1024) uint8_t g_a[(size_t)SEQ * KA * 2];
__device__ __align__(1024) float g_acc[(size_t)SEQ * DM];
__device__ unsigned g_fq[NSEG * NH];
__device__ unsigned g_fh[128];
__device__ unsigned g_fo[128];
__device__ unsigned g_fc[256];
__device__ __align__(1024) uint8_t g_ring[9 * RING_SLOT];
__device__ __align__(128) float g_gate[SEQ];
__device__ uint4 g_pub[64];
__device__ unsigned g_done;
__device__ int g_err;

__device__ __forceinline__ uint32_t smem_u32(const void* p) { return (uint32_t)__cvta_generic_to_shared(p); }
__device__ __forceinline__ uint32_t mapa(uint32_t a, uint32_t rank) { uint32_t r; asm volatile("mapa.shared::cluster.u32 %0, %1, %2;" : "=r"(r) : "r"(a), "r"(rank)); return r; }
__device__ __forceinline__ void mbar_init(uint32_t a, uint32_t cnt) { asm volatile("mbarrier.init.shared::cta.b64 [%0], %1;" :: "r"(a), "r"(cnt) : "memory"); }
__device__ __forceinline__ void mbar_expect_tx(uint32_t a, uint32_t bytes) { asm volatile("mbarrier.arrive.expect_tx.shared::cta.b64 _, [%0], %1;" :: "r"(a), "r"(bytes) : "memory"); }
__device__ __forceinline__ bool mbar_try(uint32_t a, uint32_t parity) {
  uint32_t ok;
  asm volatile("{ .reg .pred p; mbarrier.try_wait.parity.shared::cta.b64 p, [%1], %2; selp.u32 %0, 1, 0, p; }" : "=r"(ok) : "r"(a), "r"(parity) : "memory");
  return ok;
}
__device__ __forceinline__ bool mbar_try_cluster(uint32_t a, uint32_t parity) {
  uint32_t ok;
  asm volatile("{ .reg .pred p; mbarrier.try_wait.parity.acquire.cluster.shared::cta.b64 p, [%1], %2; selp.u32 %0, 1, 0, p; }" : "=r"(ok) : "r"(a), "r"(parity) : "memory");
  return ok;
}
__device__ __forceinline__ bool give_up(int it, int code) {
  if ((it & 1023) != 0) return false;
  if (it < SPIN_LIMIT && *reinterpret_cast<volatile int*>(&g_err) == 0) return false;
  if (it >= SPIN_LIMIT) g_err = code;
  return true;
}
__device__ __forceinline__ void mbar_wait(uint32_t a, uint32_t parity) {
  int it = 0;
  while (!mbar_try(a, parity)) { if (give_up(++it, 1)) break; }
}
__device__ __forceinline__ void mbar_wait1(uint32_t a, uint32_t parity) {
  asm volatile("{ .reg .pred p; .reg .u32 c; mov.u32 c, 0;\nW: mbarrier.try_wait.parity.shared::cta.b64 p, [%0], %1;\n"
               "add.u32 c, c, 1; setp.lt.and.u32 p, c, 65536, !p; @p bra W; }" :: "r"(a), "r"(parity) : "memory");
}
__device__ __forceinline__ void mbar_wait_cluster(uint32_t a, uint32_t parity) {
  int it = 0;
  while (!mbar_try_cluster(a, parity)) { if (give_up(++it, 2)) break; }
}
template <int ID, int N> __device__ __forceinline__ void bar_sync() { asm volatile("bar.sync %0, %1;" :: "n"(ID), "n"(N) : "memory"); }
template <int ID, int N> __device__ __forceinline__ void bar_arrive() { asm volatile("bar.arrive %0, %1;" :: "n"(ID), "n"(N) : "memory"); }
__device__ __forceinline__ void bar_sync_id(int id, int n) { asm volatile("bar.sync %0, %1;" :: "r"(id), "r"(n) : "memory"); }
__device__ __forceinline__ void tma2d(uint32_t dst, const CUtensorMap* tm, int c0, int c1, uint32_t mb) {
  asm volatile("cp.async.bulk.tensor.2d.shared::cluster.global.mbarrier::complete_tx::bytes [%0], [%1, {%3, %4}], [%2];"
               :: "r"(dst), "l"((uint64_t)tm), "r"(mb), "r"(c0), "r"(c1) : "memory");
}
__device__ __forceinline__ void bulk_g2s(uint32_t dst, const void* src, uint32_t bytes, uint32_t mb) {
  asm volatile("cp.async.bulk.shared::cluster.global.mbarrier::complete_tx::bytes [%0], [%1], %2, [%3];"
               :: "r"(dst), "l"(src), "r"(bytes), "r"(mb) : "memory");
}
__device__ __forceinline__ void ldm4(uint32_t* r, uint32_t a) {
  asm volatile("ldmatrix.sync.aligned.m8n8.x4.shared.b16 {%0,%1,%2,%3}, [%4];" : "=r"(r[0]), "=r"(r[1]), "=r"(r[2]), "=r"(r[3]) : "r"(a) : "memory");
}
__device__ __forceinline__ void ldm4t(uint32_t* r, uint32_t a) {
  asm volatile("ldmatrix.sync.aligned.m8n8.x4.trans.shared.b16 {%0,%1,%2,%3}, [%4];" : "=r"(r[0]), "=r"(r[1]), "=r"(r[2]), "=r"(r[3]) : "r"(a) : "memory");
}
__device__ __forceinline__ void stm4(uint32_t a, uint32_t r0, uint32_t r1, uint32_t r2, uint32_t r3) {
  asm volatile("stmatrix.sync.aligned.m8n8.x4.shared.b16 [%0], {%1,%2,%3,%4};" :: "r"(a), "r"(r0), "r"(r1), "r"(r2), "r"(r3) : "memory");
}
__device__ __forceinline__ void mma16(float* d, uint32_t a0, uint32_t a1, uint32_t a2, uint32_t a3, uint32_t b0, uint32_t b1) {
  asm volatile("mma.sync.aligned.m16n8k16.row.col.f32.bf16.bf16.f32 {%0,%1,%2,%3}, {%4,%5,%6,%7}, {%8,%9}, {%0,%1,%2,%3};"
               : "+f"(d[0]), "+f"(d[1]), "+f"(d[2]), "+f"(d[3]) : "r"(a0), "r"(a1), "r"(a2), "r"(a3), "r"(b0), "r"(b1));
}
__device__ __forceinline__ void mma16z(float* d, uint32_t a0, uint32_t a1, uint32_t a2, uint32_t a3, uint32_t b0, uint32_t b1) {
  asm volatile("mma.sync.aligned.m16n8k16.row.col.f32.bf16.bf16.f32 {%0,%1,%2,%3}, {%4,%5,%6,%7}, {%8,%9}, {%10,%10,%10,%10};"
               : "=f"(d[0]), "=f"(d[1]), "=f"(d[2]), "=f"(d[3]) : "r"(a0), "r"(a1), "r"(a2), "r"(a3), "r"(b0), "r"(b1), "f"(0.f));
}
__device__ __forceinline__ void mma8(float* d, uint32_t a0, uint32_t a1, uint32_t b0) {
  asm volatile("mma.sync.aligned.m16n8k8.row.col.f32.bf16.bf16.f32 {%0,%1,%2,%3}, {%4,%5}, {%6}, {%0,%1,%2,%3};"
               : "+f"(d[0]), "+f"(d[1]), "+f"(d[2]), "+f"(d[3]) : "r"(a0), "r"(a1), "r"(b0));
}
__device__ __forceinline__ void mma8z(float* d, uint32_t a0, uint32_t a1, uint32_t b0) {
  asm volatile("mma.sync.aligned.m16n8k8.row.col.f32.bf16.bf16.f32 {%0,%1,%2,%3}, {%4,%5}, {%6}, {%7,%7,%7,%7};"
               : "=f"(d[0]), "=f"(d[1]), "=f"(d[2]), "=f"(d[3]) : "r"(a0), "r"(a1), "r"(b0), "f"(0.f));
}
__device__ __forceinline__ uint32_t pack_bf16(float lo, float hi) { uint32_t r; asm("cvt.rn.bf16x2.f32 %0, %1, %2;" : "=r"(r) : "f"(hi), "f"(lo)); return r; }
__device__ __forceinline__ uint32_t pack_f16(float lo, float hi) { uint32_t r; asm("cvt.rn.f16x2.f32 %0, %1, %2;" : "=r"(r) : "f"(hi), "f"(lo)); return r; }
__device__ __forceinline__ float2 unpack_f16(uint32_t v) { return __half22float2(*reinterpret_cast<__half2*>(&v)); }
__device__ __forceinline__ uint32_t absmax2(uint32_t a, uint32_t b) { uint32_t r; asm("max.xorsign.abs.bf16x2 %0, %1, %2;" : "=r"(r) : "r"(a), "r"(b)); return r; }
__device__ __forceinline__ uint32_t fold_absmax(uint32_t m) { m &= 0x7FFF7FFFu; return max(m & 0xFFFFu, m >> 16); }
__device__ __forceinline__ float ex2(float x) { float r; asm("ex2.approx.ftz.f32 %0, %1;" : "=f"(r) : "f"(x)); return r; }
__device__ __forceinline__ void sts32(uint32_t a, uint32_t v) { asm volatile("st.shared.u32 [%0], %1;" :: "r"(a), "r"(v) : "memory"); }
__device__ __forceinline__ void sts64f(uint32_t a, float x, float y) { asm volatile("st.shared.v2.f32 [%0], {%1,%2};" :: "r"(a), "f"(x), "f"(y) : "memory"); }
__device__ __forceinline__ float2 lds64f(uint32_t a) { float2 v; asm volatile("ld.shared.v2.f32 {%0,%1}, [%2];" : "=f"(v.x), "=f"(v.y) : "r"(a) : "memory"); return v; }
__device__ __forceinline__ uint32_t lds32(uint32_t a) { uint32_t v; asm volatile("ld.shared.u32 %0, [%1];" : "=r"(v) : "r"(a) : "memory"); return v; }
__device__ __forceinline__ uint4 lds128(uint32_t a) { uint4 v; asm volatile("ld.shared.v4.u32 {%0,%1,%2,%3}, [%4];" : "=r"(v.x), "=r"(v.y), "=r"(v.z), "=r"(v.w) : "r"(a) : "memory"); return v; }
__device__ __forceinline__ void st_async32(uint32_t a, uint32_t v, uint32_t mb) {
  asm volatile("st.async.weak.shared::cluster.mbarrier::complete_tx::bytes.b32 [%0], %1, [%2];" :: "r"(a), "r"(v), "r"(mb) : "memory");
}
__device__ __forceinline__ void st_async64(uint32_t a, uint32_t x, uint32_t y, uint32_t mb) {
  asm volatile("st.async.weak.shared::cluster.mbarrier::complete_tx::bytes.v2.b32 [%0], {%1,%2}, [%3];" :: "r"(a), "r"(x), "r"(y), "r"(mb) : "memory");
}
__device__ __forceinline__ void st_async128(uint32_t a, uint32_t x, uint32_t y, uint32_t z, uint32_t w, uint32_t mb) {
  asm volatile("st.async.weak.shared::cluster.mbarrier::complete_tx::bytes.v4.b32 [%0], {%1,%2,%3,%4}, [%5];" :: "r"(a), "r"(x), "r"(y), "r"(z), "r"(w), "r"(mb) : "memory");
}
__device__ __forceinline__ void sts128(uint32_t a, uint32_t x, uint32_t y, uint32_t z, uint32_t w) {
  asm volatile("st.shared.v4.u32 [%0], {%1,%2,%3,%4};" :: "r"(a), "r"(x), "r"(y), "r"(z), "r"(w) : "memory");
}
__device__ __forceinline__ void lds128r(uint32_t* r, uint32_t a) {
  asm volatile("ld.shared.v4.u32 {%0,%1,%2,%3}, [%4];" : "=r"(r[0]), "=r"(r[1]), "=r"(r[2]), "=r"(r[3]) : "r"(a) : "memory");
}
__device__ __forceinline__ float4 lds128f(uint32_t a) { float4 v; asm volatile("ld.shared.v4.f32 {%0,%1,%2,%3}, [%4];" : "=f"(v.x), "=f"(v.y), "=f"(v.z), "=f"(v.w) : "r"(a) : "memory"); return v; }
__device__ __forceinline__ void mbar_arrive(uint32_t a) { asm volatile("mbarrier.arrive.shared::cta.b64 _, [%0];" :: "r"(a) : "memory"); }
__device__ __forceinline__ uint32_t movm(uint32_t a) { uint32_t d; asm volatile("movmatrix.sync.aligned.m8n8.trans.b16 %0, %1;" : "=r"(d) : "r"(a)); return d; }
__device__ __forceinline__ float rcp(float x) { float r; asm("rcp.approx.ftz.f32 %0, %1;" : "=f"(r) : "f"(x)); return r; }
__device__ __forceinline__ uint32_t f16_to_bf16(uint32_t v) { const float2 f = unpack_f16(v); return pack_bf16(f.x, f.y); }
__device__ __forceinline__ uint4 ldv128(const void* p) {
  uint4 v; asm volatile("ld.volatile.global.v4.u32 {%0,%1,%2,%3}, [%4];" : "=r"(v.x), "=r"(v.y), "=r"(v.z), "=r"(v.w) : "l"(p) : "memory"); return v;
}
__device__ __forceinline__ uint32_t ldv32(const void* p) { uint32_t v; asm volatile("ld.volatile.global.u32 %0, [%1];" : "=r"(v) : "l"(p) : "memory"); return v; }
__device__ __forceinline__ float bf_lo(uint32_t v) { return __uint_as_float(v << 16); }
__device__ __forceinline__ float bf_hi(uint32_t v) { return __uint_as_float(v & 0xFFFF0000u); }

__device__ __forceinline__ void wgmma_rs192(float* d, uint32_t a0, uint32_t a1, uint32_t a2, uint32_t a3, uint64_t desc, int acc) {
  asm volatile("{ .reg .pred p; setp.ne.b32 p, %101, 0;\n"
    "wgmma.mma_async.sync.aligned.m64n192k16.f32.bf16.bf16 {%0,%1,%2,%3,%4,%5,%6,%7,%8,%9,%10,%11,%12,%13,%14,%15,%16,%17,%18,%19,%20,%21,%22,%23,%24,%25,%26,%27,%28,%29,%30,%31,%32,%33,%34,%35,%36,%37,%38,%39,%40,%41,%42,%43,%44,%45,%46,%47,%48,%49,%50,%51,%52,%53,%54,%55,%56,%57,%58,%59,%60,%61,%62,%63,%64,%65,%66,%67,%68,%69,%70,%71,%72,%73,%74,%75,%76,%77,%78,%79,%80,%81,%82,%83,%84,%85,%86,%87,%88,%89,%90,%91,%92,%93,%94,%95}, {%96,%97,%98,%99}, %100, p, 1, 1, 1; }"
    :
      "+f"(d[0]), "+f"(d[1]), "+f"(d[2]), "+f"(d[3]), "+f"(d[4]), "+f"(d[5]), "+f"(d[6]), "+f"(d[7]), "+f"(d[8]), "+f"(d[9]), "+f"(d[10]), "+f"(d[11]),
      "+f"(d[12]), "+f"(d[13]), "+f"(d[14]), "+f"(d[15]), "+f"(d[16]), "+f"(d[17]), "+f"(d[18]), "+f"(d[19]), "+f"(d[20]), "+f"(d[21]), "+f"(d[22]), "+f"(d[23]),
      "+f"(d[24]), "+f"(d[25]), "+f"(d[26]), "+f"(d[27]), "+f"(d[28]), "+f"(d[29]), "+f"(d[30]), "+f"(d[31]), "+f"(d[32]), "+f"(d[33]), "+f"(d[34]), "+f"(d[35]),
      "+f"(d[36]), "+f"(d[37]), "+f"(d[38]), "+f"(d[39]), "+f"(d[40]), "+f"(d[41]), "+f"(d[42]), "+f"(d[43]), "+f"(d[44]), "+f"(d[45]), "+f"(d[46]), "+f"(d[47]),
      "+f"(d[48]), "+f"(d[49]), "+f"(d[50]), "+f"(d[51]), "+f"(d[52]), "+f"(d[53]), "+f"(d[54]), "+f"(d[55]), "+f"(d[56]), "+f"(d[57]), "+f"(d[58]), "+f"(d[59]),
      "+f"(d[60]), "+f"(d[61]), "+f"(d[62]), "+f"(d[63]), "+f"(d[64]), "+f"(d[65]), "+f"(d[66]), "+f"(d[67]), "+f"(d[68]), "+f"(d[69]), "+f"(d[70]), "+f"(d[71]),
      "+f"(d[72]), "+f"(d[73]), "+f"(d[74]), "+f"(d[75]), "+f"(d[76]), "+f"(d[77]), "+f"(d[78]), "+f"(d[79]), "+f"(d[80]), "+f"(d[81]), "+f"(d[82]), "+f"(d[83]),
      "+f"(d[84]), "+f"(d[85]), "+f"(d[86]), "+f"(d[87]), "+f"(d[88]), "+f"(d[89]), "+f"(d[90]), "+f"(d[91]), "+f"(d[92]), "+f"(d[93]), "+f"(d[94]), "+f"(d[95])
    : "r"(a0), "r"(a1), "r"(a2), "r"(a3), "l"(desc), "r"(acc));
}

__device__ __forceinline__ void wgmma_rs256(float* d, uint32_t a0, uint32_t a1, uint32_t a2, uint32_t a3, uint64_t desc, int acc) {
  asm volatile("{ .reg .pred p; setp.ne.b32 p, %133, 0;\n"
    "wgmma.mma_async.sync.aligned.m64n256k16.f32.bf16.bf16 {%0,%1,%2,%3,%4,%5,%6,%7,%8,%9,%10,%11,%12,%13,%14,%15,%16,%17,%18,%19,%20,%21,%22,%23,%24,%25,%26,%27,%28,%29,%30,%31,%32,%33,%34,%35,%36,%37,%38,%39,%40,%41,%42,%43,%44,%45,%46,%47,%48,%49,%50,%51,%52,%53,%54,%55,%56,%57,%58,%59,%60,%61,%62,%63,%64,%65,%66,%67,%68,%69,%70,%71,%72,%73,%74,%75,%76,%77,%78,%79,%80,%81,%82,%83,%84,%85,%86,%87,%88,%89,%90,%91,%92,%93,%94,%95,%96,%97,%98,%99,%100,%101,%102,%103,%104,%105,%106,%107,%108,%109,%110,%111,%112,%113,%114,%115,%116,%117,%118,%119,%120,%121,%122,%123,%124,%125,%126,%127}, {%128,%129,%130,%131}, %132, p, 1, 1, 1; }"
    :
      "+f"(d[0]), "+f"(d[1]), "+f"(d[2]), "+f"(d[3]), "+f"(d[4]), "+f"(d[5]), "+f"(d[6]), "+f"(d[7]), "+f"(d[8]), "+f"(d[9]), "+f"(d[10]), "+f"(d[11]),
      "+f"(d[12]), "+f"(d[13]), "+f"(d[14]), "+f"(d[15]), "+f"(d[16]), "+f"(d[17]), "+f"(d[18]), "+f"(d[19]), "+f"(d[20]), "+f"(d[21]), "+f"(d[22]), "+f"(d[23]),
      "+f"(d[24]), "+f"(d[25]), "+f"(d[26]), "+f"(d[27]), "+f"(d[28]), "+f"(d[29]), "+f"(d[30]), "+f"(d[31]), "+f"(d[32]), "+f"(d[33]), "+f"(d[34]), "+f"(d[35]),
      "+f"(d[36]), "+f"(d[37]), "+f"(d[38]), "+f"(d[39]), "+f"(d[40]), "+f"(d[41]), "+f"(d[42]), "+f"(d[43]), "+f"(d[44]), "+f"(d[45]), "+f"(d[46]), "+f"(d[47]),
      "+f"(d[48]), "+f"(d[49]), "+f"(d[50]), "+f"(d[51]), "+f"(d[52]), "+f"(d[53]), "+f"(d[54]), "+f"(d[55]), "+f"(d[56]), "+f"(d[57]), "+f"(d[58]), "+f"(d[59]),
      "+f"(d[60]), "+f"(d[61]), "+f"(d[62]), "+f"(d[63]), "+f"(d[64]), "+f"(d[65]), "+f"(d[66]), "+f"(d[67]), "+f"(d[68]), "+f"(d[69]), "+f"(d[70]), "+f"(d[71]),
      "+f"(d[72]), "+f"(d[73]), "+f"(d[74]), "+f"(d[75]), "+f"(d[76]), "+f"(d[77]), "+f"(d[78]), "+f"(d[79]), "+f"(d[80]), "+f"(d[81]), "+f"(d[82]), "+f"(d[83]),
      "+f"(d[84]), "+f"(d[85]), "+f"(d[86]), "+f"(d[87]), "+f"(d[88]), "+f"(d[89]), "+f"(d[90]), "+f"(d[91]), "+f"(d[92]), "+f"(d[93]), "+f"(d[94]), "+f"(d[95]),
      "+f"(d[96]), "+f"(d[97]), "+f"(d[98]), "+f"(d[99]), "+f"(d[100]), "+f"(d[101]), "+f"(d[102]), "+f"(d[103]), "+f"(d[104]), "+f"(d[105]), "+f"(d[106]), "+f"(d[107]),
      "+f"(d[108]), "+f"(d[109]), "+f"(d[110]), "+f"(d[111]), "+f"(d[112]), "+f"(d[113]), "+f"(d[114]), "+f"(d[115]), "+f"(d[116]), "+f"(d[117]), "+f"(d[118]), "+f"(d[119]),
      "+f"(d[120]), "+f"(d[121]), "+f"(d[122]), "+f"(d[123]), "+f"(d[124]), "+f"(d[125]), "+f"(d[126]), "+f"(d[127])
    : "r"(a0), "r"(a1), "r"(a2), "r"(a3), "l"(desc), "r"(acc));
}

__device__ __forceinline__ void wg_fence() { asm volatile("wgmma.fence.sync.aligned;" ::: "memory"); }
__device__ __forceinline__ void wg_commit() { asm volatile("wgmma.commit_group.sync.aligned;" ::: "memory"); }
template <int N> __device__ __forceinline__ void wg_wait() { asm volatile("wgmma.wait_group.sync.aligned %0;" :: "n"(N) : "memory"); }
__device__ __forceinline__ void tma5d(uint32_t dst, const CUtensorMap* tm, int c0, int c4, uint32_t mb) {
  asm volatile("cp.async.bulk.tensor.5d.shared::cluster.global.mbarrier::complete_tx::bytes [%0], [%1, {%3, %5, %5, %5, %4}], [%2];"
               :: "r"(dst), "l"((uint64_t)tm), "r"(mb), "r"(c0), "r"(c4), "r"(0) : "memory");
}
__device__ __forceinline__ void tma5d_mc(uint32_t dst, const CUtensorMap* tm, int c0, int c4, uint32_t mb) {
  asm volatile("cp.async.bulk.tensor.5d.shared::cluster.global.mbarrier::complete_tx::bytes.multicast::cluster [%0], [%1, {%3, %5, %5, %5, %4}], [%2], %6;"
               :: "r"(dst), "l"((uint64_t)tm), "r"(mb), "r"(c0), "r"(c4), "r"(0), "h"((unsigned short)3) : "memory");
}
__device__ __forceinline__ void mbar_arrive_cluster(uint32_t a) { asm volatile("mbarrier.arrive.shared::cluster.b64 _, [%0];" :: "r"(a) : "memory"); }
__device__ __forceinline__ void ldg128(uint32_t* r, const uint8_t* p) {
  asm volatile("ld.global.L1::no_allocate.v4.u32 {%0,%1,%2,%3}, [%4];" : "=r"(r[0]), "=r"(r[1]), "=r"(r[2]), "=r"(r[3]) : "l"(p) : "memory");
}
__device__ __forceinline__ uint32_t ld_relaxed(const unsigned* p) { uint32_t v; asm volatile("ld.relaxed.gpu.global.u32 %0, [%1];" : "=r"(v) : "l"(p) : "memory"); return v; }
__device__ __forceinline__ uint32_t ld_acquire(const unsigned* p) { uint32_t v; asm volatile("ld.acquire.gpu.global.u32 %0, [%1];" : "=r"(v) : "l"(p) : "memory"); return v; }
__device__ __forceinline__ void red_release(unsigned* p) { asm volatile("red.release.gpu.global.add.u32 [%0], 1;" :: "l"(p) : "memory"); }
__device__ __forceinline__ void red_relaxed(unsigned* p) { asm volatile("red.relaxed.gpu.global.add.u32 [%0], 1;" :: "l"(p) : "memory"); }
__device__ __forceinline__ void fence_gpu() { asm volatile("fence.acq_rel.gpu;" ::: "memory"); }
__device__ __forceinline__ void wait_count(const unsigned* p, uint32_t target) {
  int it = 0;
  while (__any_sync(~0u, (int)(ld_acquire(p) - target) < 0)) { if (give_up(++it, 5)) break; __nanosleep(64); }
}

constexpr int G_ST = 32768, G_NST = 7, G_MB = G_ST * G_NST, GB_W = G_MB  , GB_FULL = G_MB + 32, GB_EMPTY = G_MB + 96, G_SMEM = G_MB + 160;

constexpr int C_WV = 0, C_WO = 65536, C_KVQ = 131072, KVQ_ST = 20480, C_QM = 192512, C_OT = 194560, C_KM = 196608,
              KM_BUF = 8192  , C_MEM = 212992  , C_SX = 221184  , C_MISC = 225280;
constexpr int MB_WQ = C_MISC, MB_WK = C_MISC + 8, MB_WV = C_MISC + 16, MB_WO = C_MISC + 24, MB_MR = C_MISC + 48  ,
              MB_S = C_MISC + 64, MB_V = C_MISC + 72, MB_KVQ = C_MISC + 80  ;
constexpr int TX_S = 4096, TX_V = 4096 + 2048 + 64;
constexpr int C_WE = C_MISC + 112;
constexpr int C_MX = C_MISC + 128;
constexpr int C_WM = C_MISC + 192;
constexpr int C_XE = C_MISC + 256;
constexpr int C_SU = C_MISC + 704;
constexpr int C_DBG = C_MISC + 768;
constexpr int C_SMEM = C_DBG;
#define STAMP(slot)
#define STAMP2(slot)
#define STAMP_NEXT

__device__ __forceinline__ int fresh(int v) { asm volatile("" : "+r"(v)); return v; }

struct Args {
  CUtensorMap tmq, tmk, tmv, tmo;
  CUtensorMap pw[3];
  CUtensorMap pb[4];
  const bf16* x; const bf16* mem0; const bf16* wo; const bf16* gate_w; bf16* out;
  uint32_t zero;
  uint16_t first[NGC + 2];
  uint32_t job[MAXJOBS];
};
constexpr int K_SMEM = C_SMEM > G_SMEM ? C_SMEM : G_SMEM;

__device__ __forceinline__ void load_a(uint32_t* a, const uint8_t* p0, const uint8_t* p1, int d = 64) {
  ldg128(a, p0); ldg128(a + 4, p1); ldg128(a + 8, p0 + d); ldg128(a + 12, p1 + d);
}
__device__ __forceinline__ void frag_a(uint32_t* u, const uint32_t* a, uint32_t z) {
#pragma unroll
  for (int i = 0; i < 16; i++) { u[i] = a[(i & 8) | ((i & 1) << 2) | (i & 2) | ((i >> 2) & 1)] ^ z; asm volatile("" : "+r"(u[i])); }
}
#define GSTAMP(i)
#define QSTAMP(it, k)

__global__ void __launch_bounds__(384, 1)
fused_kernel(const __grid_constant__ Args args) {
  extern __shared__ __align__(1024) uint8_t smem[];
  const int tid = threadIdx.x;
  const int lane = __shfl_sync(~0u, tid & 31, tid & 31);
  const int warp = __shfl_sync(~0u, tid >> 5, 0);
  const int cta = blockIdx.x, h = (cta >> 1) & 31, j = cta & 1;
  const uint32_t sb = smem_u32(smem);

  if (tid == 0 && cta >= 64) {
    for (int i = 0; i < 4; i++) mbar_init(sb + GB_W + 8 * i, 1);
    for (int i = 0; i < G_NST; i++) { mbar_init(sb + GB_FULL + 8 * i, 1); mbar_init(sb + GB_EMPTY + 8 * i, 16); }
    asm volatile("fence.mbarrier_init.release.cluster;" ::: "memory");
    if (cta < 128)
      for (int i = 0; i < 4; i++) {
        mbar_expect_tx(sb + GB_W + 8 * i, 49152);
        for (int b = 0; b < 3; b++) tma5d(sb + b * 65536 + i * 16384, &args.pw[b], h * DH + j * 64, 4 * i, sb + GB_W + 8 * i);
      }
  }
  if (tid == 0 && cta < 64) {
    mbar_init(sb + MB_WQ, 1); mbar_init(sb + MB_WK, 1); mbar_init(sb + MB_WV, 1); mbar_init(sb + MB_WO, 1);
    mbar_init(sb + MB_MR, 1); mbar_init(sb + MB_MR + 8, 1);
    mbar_init(sb + MB_S, 1); mbar_init(sb + MB_V, 1);
    for (int i = 0; i < 3; i++) mbar_init(sb + MB_KVQ + 8 * i, 1);
    asm volatile("fence.mbarrier_init.release.cluster;" ::: "memory");
    const int col = h * DH + j * 64;
    mbar_expect_tx(sb + MB_WQ, 65536); tma2d(sb + C_WO, &args.tmq, col, 0, sb + MB_WQ); tma2d(sb + C_WO + 32768, &args.tmq, col, 256, sb + MB_WQ);
    mbar_expect_tx(sb + MB_WK, 65536); tma2d(sb + C_KVQ, &args.tmk, col, 0, sb + MB_WK); tma2d(sb + C_KVQ + 32768, &args.tmk, col, 256, sb + MB_WK);
    mbar_expect_tx(sb + MB_WV, 65536); tma2d(sb + C_WV, &args.tmv, col, 0, sb + MB_WV); tma2d(sb + C_WV + 32768, &args.tmv, col, 256, sb + MB_WV);
    mbar_expect_tx(sb + MB_MR, 2048); mbar_expect_tx(sb + MB_MR + 8, 2048); mbar_expect_tx(sb + MB_S, TX_S); mbar_expect_tx(sb + MB_V, TX_V);
  }
  const uint32_t tag = ldv32(&g_done) / NCTA + 1;
  asm volatile("barrier.cluster.arrive.aligned; barrier.cluster.wait.aligned;" ::: "memory");
  uint8_t* const ring = reinterpret_cast<uint8_t*>((reinterpret_cast<uintptr_t>(g_ring) + RING_SLOT - 1) & ~(uintptr_t)(RING_SLOT - 1));
  auto issue_stage = [&](int seg, int stg) {
    const uint32_t mb = sb + MB_KVQ + 8 * stg;
    mbar_expect_tx(mb, KVQ_ST);
    bulk_g2s(sb + C_KVQ + stg * KVQ_ST, g_qkv + (size_t)(seg * NH + h) * BLK_BYTES + j * 4096, KVQ_ST, mb);
  };

  if (cta >= 64 && warp < 8) {
    asm volatile("setmaxnreg.inc.sync.aligned.u32 232;");
    const int wg = warp >> 2, w = warp & 3, g = lane >> 2, t = lane & 3;
    const uint64_t dsc_hi = (uint64_t)((2048 >> 4) | (1u << 30)) << 32;
    uint32_t A[4][16], U[2][16];
    GSTAMP(0);
    if (cta < 128) {
      float acc[96];
      const uint8_t* p0 = reinterpret_cast<const uint8_t*>(args.x) + (size_t)(wg * 64 + w * 16 + g) * (DM * 2) + t * 16;
#pragma unroll
      for (int i = 0; i < 4; i++) load_a(A[i], p0 + i * 128, p0 + i * 128 + 8192);
      const uint64_t dsc = dsc_hi | (uint64_t)(((sb >> 4) & 0x3FFF) | ((65536 >> 4) << 16));
      uint8_t* dst = g_qkv + (size_t)((2 * wg + (w >> 1)) * NH + h) * BLK_BYTES + 4096 + (w & 1) * 4096 + j * 1024 + g * 64 + ((t ^ (g >> 1)) << 4);
      const int dq = (w & 1) * 16384 - 4096;
      unsigned* fl = g_fq + (2 * wg + (w >> 1)) * NH + h;
      if (wg == 1) bar_sync<1, 256>();
      for (int it = 0; it < 16; it++) {
        QSTAMP(it, 0);
#pragma unroll
        for (int kc = 0; kc < 8; kc++) {
          if (it == 0) mbar_wait(sb + GB_W + 8 * (kc >> 1), 0);
          uint32_t* a = U[kc & 1];
          frag_a(a, A[kc & 3], args.zero);
          wg_fence();
          wgmma_rs192(acc, a[0], a[1], a[2], a[3], dsc + kc * 512, kc != 0);
          wgmma_rs192(acc, a[4], a[5], a[6], a[7], dsc + kc * 512 + 64, 1);
          wgmma_rs192(acc, a[8], a[9], a[10], a[11], dsc + kc * 512 + 256, 1);
          wgmma_rs192(acc, a[12], a[13], a[14], a[15], dsc + kc * 512 + 320, 1);
          wg_commit();
          const uint8_t* pn = p0 + (kc < 4 ? (kc + 4) * 128 : 128 * DM * 2 + (kc - 4) * 128);
          if (kc < 4 || it < 15) load_a(A[kc & 3], pn, pn + 8192);
          if (kc == 0 && it > 0) { __syncwarp(); if (lane == 0) red_release(fl - 4 * NH); }
          if (kc == 0) { QSTAMP(it, 1); }
          if (kc == 4) { QSTAMP(it, 4); }
          if (kc == 3 && it == 0 && wg == 0) bar_arrive<1, 256>();
          wg_wait<1>();
        }
        wg_wait<0>();
        QSTAMP(it, 2);
#pragma unroll
        for (int b = 0; b < 6; b++) {
          const float* d = acc + 16 * b;
          uint8_t* q = dst + (b < 4 ? (b >> 1) * 8192 : dq) + (b & 1) * 512;
          *reinterpret_cast<uint4*>(q) = make_uint4(pack_bf16(d[0], d[1]), pack_bf16(d[4], d[5]), pack_bf16(d[8], d[9]), pack_bf16(d[12], d[13]));
          *reinterpret_cast<uint4*>(q + 2048) = make_uint4(pack_bf16(d[2], d[3]), pack_bf16(d[6], d[7]), pack_bf16(d[10], d[11]), pack_bf16(d[14], d[15]));
        }
        QSTAMP(it, 3);
        p0 += 128 * DM * 2; dst += (size_t)4 * NH * BLK_BYTES; fl += 4 * NH;
      }
      __syncwarp();
      if (lane == 0) red_release(fl - 4 * NH);
    }
    GSTAMP(1);
    const uint32_t ea = mapa(sb + GB_EMPTY, lane & 1);
    if (lane < 2 * G_NST) mbar_arrive_cluster(ea + 8 * (lane >> 1));
    const int gc = (cta - 64) >> 1;
    const int jn = args.first[gc + 1];
    int ji = args.first[gc];
    const uint64_t dsc = dsc_hi | (uint64_t)(((sb >> 4) & 0x3FFF) | ((8192 >> 4) << 16));
    uint32_t st = 0, ph = 0;
    bool loaded = false, gate_ok = false;
    const uint8_t *p0, *p1;
    int ad;
    auto set_a = [&](uint32_t job) {
      const int m16 = ((job >> 1) & 7) * 16 + j * 8 + warp;
      const bool fin = job & 1;
      p0 = fin ? g_a + (size_t)m16 * A_TILE + ((job >> 8) & 127) * 2048 + lane * 16
               : reinterpret_cast<const uint8_t*>(args.x) + (size_t)(m16 * 16 + g) * (DM * 2) + t * 16;
      p1 = p0 + (fin ? 512 : 8 * DM * 2);
      ad = fin ? 1024 : 64;
    };
    auto dep_ptr = [&](uint32_t job) { return (((job >> 8) & 127) < 64 ? g_fo : g_fh) + ((job >> 1) & 7) * 16 + j * 8 + warp; };
    auto dep_cnt = [&](uint32_t job) { return tag * (((job >> 8) & 127) < 64 ? 32u : 14u); };
    if (wg == 1) bar_sync<2, 256>();
    bool lead = wg == 0;
    float acc[128];
    for (; ji < jn; ji++) {
      const uint32_t job = args.job[ji];
      if (!loaded) {
        if (job & 1) wait_count(dep_ptr(job), dep_cnt(job));
        set_a(job);
        load_a(A[0], p0, p1, ad); load_a(A[1], p0 + 2 * ad, p1 + 2 * ad, ad);
      }
      QSTAMP(16 + ji - args.first[gc], 0);
      const uint32_t nxt = args.job[ji + 1];
      const uint32_t dep = ld_relaxed(dep_ptr(nxt));
      const int nk = (job >> 15) & 127;
      uint32_t pst = 0;
      for (int k = 0; k < nk; k += 2) {
#pragma unroll
        for (int u = 0; u < 2; u++) {
          uint32_t* a = U[u];
          mbar_wait(sb + GB_FULL + 8 * st, ph);
          frag_a(a, A[u], args.zero);
          const uint64_t d = dsc + st * (G_ST >> 4);
          wg_fence();
          wgmma_rs256(acc, a[0], a[1], a[2], a[3], d, u != 0 || k != 0);
          wgmma_rs256(acc, a[4], a[5], a[6], a[7], d + 64, 1);
          wgmma_rs256(acc, a[8], a[9], a[10], a[11], d + 256, 1);
          wgmma_rs256(acc, a[12], a[13], a[14], a[15], d + 320, 1);
          wg_commit();
          if (k + 2 < nk) load_a(A[u], p0 + (2 * u + 4) * ad, p1 + (2 * u + 4) * ad, ad);
          if (u == 0 && k == 2 && lead) { bar_arrive<2, 256>(); lead = false; }
          wg_wait<1>();
          if ((u != 0 || k != 0) && lane < 2) mbar_arrive_cluster(ea + 8 * pst);
          pst = st;
          if (++st == G_NST) { st = 0; ph ^= 1; }
        }
        p0 += 4 * ad; p1 += 4 * ad;
      }
      wg_wait<0>();
      QSTAMP(16 + ji - args.first[gc], 2);
      if (lane < 2) mbar_arrive_cluster(ea + 8 * pst);
      loaded = ji + 1 < jn && (!(nxt & 1) || (int)(dep - dep_cnt(nxt)) >= 0);
      if (loaded) {
        if (nxt & 1) fence_gpu();
        set_a(nxt);
        load_a(A[0], p0, p1, ad); load_a(A[1], p0 + 2 * ad, p1 + 2 * ad, ad);
      }
      QSTAMP(16 + ji - args.first[gc], 1);
      const int m16 = ((job >> 1) & 7) * 16 + j * 8 + warp, n = (job >> 4) & 15;
      const int row = m16 * 16 + g;
      if (!(job & 1)) {
        if (!gate_ok) {
          int it = 0;
          while (!__all_sync(~0u, ldv32(&g_pub[lane]) == tag && ldv32(&g_pub[lane + 32]) == tag)) { if (give_up(++it, 6)) break; }
          fence_gpu();
          gate_ok = true;
        }
        const float s0 = 1.0f - __ldcg(g_gate + row), s1 = 1.0f - __ldcg(g_gate + row + 8);
        uint8_t* q = g_a + (size_t)m16 * A_TILE + (HD / 32 + n * 4) * 1024 + lane * 16;
#pragma unroll
        for (int b = 0; b < 4; b++) {
          uint32_t lo[4], hi[4];
#pragma unroll
          for (int i = 0; i < 4; i++) {
            const float* ga = acc + 16 * b + 4 * i;
            float v[4];
#pragma unroll
            for (int e = 0; e < 4; e++) v[e] = __fdividef(ga[64 + e] * (e < 2 ? s0 : s1), 1.0f + ex2(ga[e] * -1.4426950408889634f));
            lo[i] = pack_bf16(v[0], v[1]); hi[i] = pack_bf16(v[2], v[3]);
          }
          *reinterpret_cast<uint4*>(q + 1024 * b) = make_uint4(lo[0], lo[1], lo[2], lo[3]);
          *reinterpret_cast<uint4*>(q + 1024 * b + 512) = make_uint4(hi[0], hi[1], hi[2], hi[3]);
        }
        QSTAMP(16 + ji - args.first[gc], 4);
        __syncwarp();
        if (lane == 0) red_release(g_fh + m16);
      } else {
        float* q = g_acc + (size_t)row * DM + n * 256 + 2 * t;
        unsigned* fc = g_fc + m16 * 2 + n;
        const uint32_t parts = job >> 23, base = (tag - 1) * parts;
        if (job & (1u << 22)) {
#pragma unroll
          for (int i = 0; i < 32; i++) {
            *reinterpret_cast<float2*>(q + 8 * i) = make_float2(acc[4 * i], acc[4 * i + 1]);
            *reinterpret_cast<float2*>(q + 8 * i + 8 * DM) = make_float2(acc[4 * i + 2], acc[4 * i + 3]);
          }
          __syncwarp();
          if (lane == 0) red_release(fc);
        } else {
          wait_count(fc, base + 1);
#pragma unroll
          for (int i = 0; i < 32; i++) {
            asm volatile("red.relaxed.gpu.global.add.v2.f32 [%0], {%1,%2};" :: "l"(q + 8 * i), "f"(acc[4 * i]), "f"(acc[4 * i + 1]) : "memory");
            asm volatile("red.relaxed.gpu.global.add.v2.f32 [%0], {%1,%2};" :: "l"(q + 8 * i + 8 * DM), "f"(acc[4 * i + 2]), "f"(acc[4 * i + 3]) : "memory");
          }
          __syncwarp();
          uint32_t tk = 0;
          if (lane == 0) asm volatile("atom.acq_rel.gpu.global.add.u32 %0, [%1], 1;" : "=r"(tk) : "l"(fc) : "memory");
          tk = __shfl_sync(~0u, tk, 0);
          if (tk == base + parts - 1) {
            const float4* s = reinterpret_cast<const float4*>(g_acc + (size_t)m16 * 16 * DM + n * 256) + 2 * lane;
            uint4* o = reinterpret_cast<uint4*>(args.out + (size_t)m16 * 16 * DM + n * 256) + lane;
#pragma unroll
            for (int r = 0; r < 32; r++) {
              const float4 v = __ldcg(s + (r >> 1) * (DM / 4) + (r & 1));
              acc[4 * r] = v.x; acc[4 * r + 1] = v.y; acc[4 * r + 2] = v.z; acc[4 * r + 3] = v.w;
            }
#pragma unroll
            for (int r = 0; r < 16; r++) {
              const float* a = acc + 8 * r;
              o[r * (DM / 8)] = make_uint4(pack_bf16(a[0], a[1]), pack_bf16(a[2], a[3]), pack_bf16(a[4], a[5]), pack_bf16(a[6], a[7]));
            }
          }
        }
      }
      GSTAMP(2 + ji - args.first[gc]);
      QSTAMP(16 + ji - args.first[gc], 3);
    }
    if (lead) bar_arrive<2, 256>();
    asm volatile("barrier.cluster.arrive.aligned; barrier.cluster.wait.aligned;" ::: "memory");
  } else if (cta >= 64) {
    asm volatile("setmaxnreg.dec.sync.aligned.u32 40;");
    if (warp == 8 && lane == 0) {
      const int gc = (cta - 64) >> 1;
      const int jn = args.first[gc + 1];
      uint32_t st = 0, ph = 0;
      for (int ji = args.first[gc]; ji < jn; ji++) {
        const uint32_t job = args.job[ji];
        const int n = (job >> 4) & 15, k0 = (job >> 8) & 127, nk = (job >> 15) & 127;
        const CUtensorMap* tm = &args.pb[(job & 1) ? (k0 < 64 ? 2 : 3) : j];
        const int col = (job & 1) ? n * 256 + j * 128 : n * 128;
        for (int k = 0; k < nk; k++) {
          mbar_wait_cluster(sb + GB_EMPTY + 8 * st, ph);
          const uint32_t mb = sb + GB_FULL + 8 * st, dst = sb + st * G_ST + j * 16384;
          mbar_expect_tx(mb, G_ST);
          tma5d_mc(dst, tm, col, 2 * ((k0 & 63) + k), mb);
          tma5d_mc(dst + 8192, tm, col + 64, 2 * ((k0 & 63) + k), mb);
          if (++st == G_NST) { st = 0; ph ^= 1; }
        }
      }
      atomicAdd(&g_done, 1u);
    }
    __syncwarp();
    asm volatile("barrier.cluster.arrive.aligned; barrier.cluster.wait.aligned;" ::: "memory");
  } else if (warp < 8) {
    asm volatile("setmaxnreg.inc.sync.aligned.u32 " FAT_REGS ";");
    const int gam = warp >> 2, w = warp & 3;
    uint32_t wq[16][4], wk[16][4], R[16][4];
    auto w_off = [&](int l) {
      return (uint32_t)(((l & 7) + ((l >> 4) << 3)) * 128 + (((2 * w + ((l >> 3) & 1)) ^ (l & 7)) << 4) + gam * 16384 + j * 32768 + (w << 12));
    };
    auto w_frag = [&](uint32_t o, int i) { return (o ^ ((((i >> 1) & 3) << 12) | ((i >> 3) << 15))) + (i & 1) * 2048; };
    mbar_wait(sb + MB_WQ, 0);
#pragma unroll
    for (int i = 0; i < 16; i++) ldm4t(wq[i], sb + C_WO + w_frag(w_off(lane), i));
    mbar_wait(sb + MB_WK, 0);
#pragma unroll
    for (int i = 0; i < 16; i++) ldm4t(wk[i], sb + C_KVQ + w_frag(w_off(lane), i));
    bar_sync<10, 384>();
    mbar_wait(sb + MB_WV, 0);
    {
      uint32_t m = 0;
#pragma unroll
      for (int i = 0; i < 16; i++) {
        ldm4t(R[i], sb + C_WV + w_frag(w_off(lane), i));
        m = absmax2(absmax2(m, absmax2(R[i][0], R[i][1])), absmax2(R[i][2], R[i][3]));
      }
      m = __reduce_max_sync(~0u, fold_absmax(m));
      if (lane == 0) sts32(sb + C_WM + warp * 4, m);
      bar_arrive<11, 384>();
    }
    const uint32_t peer = mapa(sb, j ^ 1), self = mapa(sb, j);
    const int delay = POLL_DELAY;
    uint32_t pk[4];
#pragma unroll
    for (int i = 0; i < 4; i++)
      pk[i] = __ldg(reinterpret_cast<const uint32_t*>(args.mem0 + (lane >> 2) * DM + j * 256 + warp * 32 + i * 8 + 2 * (lane & 3)));
    mbar_wait(sb + MB_WO, 0);
    int E = 0;
    uint32_t mo = warp * 512 + lane * 16;
    for (int s = 0;; s++) {
      STAMP(0);
      st_async128(peer + C_MEM + 4096 + mo, pk[0], pk[1], pk[2], pk[3], peer + MB_MR + gam * 8);
      sts128(sb + C_MEM + mo, pk[0], pk[1], pk[2], pk[3]);
      float cq[4], ck[4], cv[4], cw[4], cx[4];
      uint32_t b[8][4], Wo[16][4];
      mma16z(ck, wk[0][0], wk[0][1], wk[0][2], wk[0][3], pk[0], pk[1]);
      mma16z(cq, wq[0][0], wq[0][1], wq[0][2], wq[0][3], pk[0], pk[1]);
      mma16z(cv, R[0][0], R[0][1], R[0][2], R[0][3], pk[0], pk[1]);
      bar_sync_id(3 + gam, 128);
      STAMP(1);
      lds128r(b[1], sb + C_MEM + (mo ^ 512));
      lds128r(b[2], sb + C_MEM + (mo ^ 1024));
      mma16(ck, wk[1][0], wk[1][1], wk[1][2], wk[1][3], pk[2], pk[3]);
      mma16(cq, wq[1][0], wq[1][1], wq[1][2], wq[1][3], pk[2], pk[3]);
      mma16(cv, R[1][0], R[1][1], R[1][2], R[1][3], pk[2], pk[3]);
      const uint32_t mx = fold_absmax(absmax2(absmax2(pk[0], pk[1]), absmax2(pk[2], pk[3])));
      lds128r(b[3], sb + C_MEM + (mo ^ 1536));
#pragma unroll
      for (int i = 1; i < 4; i++) {
        mma16(ck, wk[2 * i][0], wk[2 * i][1], wk[2 * i][2], wk[2 * i][3], b[i][0], b[i][1]);
        mma16(cq, wq[2 * i][0], wq[2 * i][1], wq[2 * i][2], wq[2 * i][3], b[i][0], b[i][1]);
        if (i < NVQ) mma16(cv, R[2 * i][0], R[2 * i][1], R[2 * i][2], R[2 * i][3], b[i][0], b[i][1]);
        if (i == 3) {
          mbar_wait1(sb + MB_MR + gam * 8, s & 1);
#pragma unroll
          for (int u = 0; u < 4; u++) lds128r(b[4 + u], sb + C_MEM + 4096 + (mo ^ (u * 512)));
        }
        mma16(ck, wk[2 * i + 1][0], wk[2 * i + 1][1], wk[2 * i + 1][2], wk[2 * i + 1][3], b[i][2], b[i][3]);
        mma16(cq, wq[2 * i + 1][0], wq[2 * i + 1][1], wq[2 * i + 1][2], wq[2 * i + 1][3], b[i][2], b[i][3]);
        if (i < NVQ) mma16(cv, R[2 * i + 1][0], R[2 * i + 1][1], R[2 * i + 1][2], R[2 * i + 1][3], b[i][2], b[i][3]);
      }
      const int la = fresh(lane);
      const uint32_t km = C_KM + (s & 1) * KM_BUF;
      uint32_t ta;
      {
        const int r = la & 7;
        ta = (2 * (w >> 1) + (r >> 2)) * 512 + ((r ^ (4 * (w & 1) + 2 * ((la >> 3) & 1))) << 4) +
             ((la & 16) ? km + j * 2048 + gam * 256 + ((r >> 1) & 1) * 128 : C_QM + gam * 128 + ((r >> 1) & 1) * 256);
        asm volatile("" : "+r"(ta));
      }
      mma16z(cx, wk[8][0], wk[8][1], wk[8][2], wk[8][3], b[4][0], b[4][1]);
      mma16z(cw, wq[8][0], wq[8][1], wq[8][2], wq[8][3], b[4][0], b[4][1]);
      mma16(ck, wk[9][0], wk[9][1], wk[9][2], wk[9][3], b[4][2], b[4][3]);
      mma16(cq, wq[9][0], wq[9][1], wq[9][2], wq[9][3], b[4][2], b[4][3]);
#pragma unroll
      for (int i = 5; i < 8; i++) {
        mma16(cx, wk[2 * i][0], wk[2 * i][1], wk[2 * i][2], wk[2 * i][3], b[i][0], b[i][1]);
        mma16(cw, wq[2 * i][0], wq[2 * i][1], wq[2 * i][2], wq[2 * i][3], b[i][0], b[i][1]);
        mma16(ck, wk[2 * i + 1][0], wk[2 * i + 1][1], wk[2 * i + 1][2], wk[2 * i + 1][3], b[i][2], b[i][3]);
        mma16(cq, wq[2 * i + 1][0], wq[2 * i + 1][1], wq[2 * i + 1][2], wq[2 * i + 1][3], b[i][2], b[i][3]);
      }
      const float up = __uint_as_float((uint32_t)(127 + E) << 23);
      const uint32_t k_lo = pack_bf16((ck[0] + cx[0]) * up, (ck[1] + cx[1]) * up), k_hi = pack_bf16((ck[2] + cx[2]) * up, (ck[3] + cx[3]) * up);
      const uint32_t q_hi = pack_bf16((cq[2] + cw[2]) * up, (cq[3] + cw[3]) * up);
      stm4(sb + ta, pack_bf16((cq[0] + cw[0]) * up, (cq[1] + cw[1]) * up), q_hi, k_lo, k_hi);
      bar_arrive<6, 384>();
      STAMP(2);
      b[NVQ][2] |= q_hi & args.zero;
      b[NVQ][0] |= q_hi & args.zero;
      mma16z(cw, R[2 * NVQ + 1][0], R[2 * NVQ + 1][1], R[2 * NVQ + 1][2], R[2 * NVQ + 1][3], b[NVQ][2], b[NVQ][3]);
      mma16(cv, R[2 * NVQ][0], R[2 * NVQ][1], R[2 * NVQ][2], R[2 * NVQ][3], b[NVQ][0], b[NVQ][1]);
#pragma unroll
      for (int i = NVQ + 1; i < 8; i++) {
        mma16(cw, R[2 * i + 1][0], R[2 * i + 1][1], R[2 * i + 1][2], R[2 * i + 1][3], b[i][2], b[i][3]);
        mma16(cv, R[2 * i][0], R[2 * i][1], R[2 * i][2], R[2 * i][3], b[i][0], b[i][1]);
      }
      {
        const int g = la >> 2;
        const uint32_t a = km + (4 * j + 2 * (w >> 1) + (g >> 2)) * 512 + gam * 256 + ((g >> 1) & 1) * 128 + ((g ^ (4 * (w & 1))) << 4) + (la & 3) * 4;
        st_async32(peer + a, k_lo, peer + MB_V);
        st_async32(peer + (a ^ 32), k_hi, peer + MB_V);
        const uint32_t d = (la & 1) ? peer : self;
        asm volatile("{ .reg .pred p; setp.lt.u32 p, %3, 2; @p st.async.weak.shared::cluster.mbarrier::complete_tx::bytes.b32 [%0], %1, [%2];\n"
                     "setp.eq.u32 p, %3, %5; @p mbarrier.arrive.expect_tx.shared::cta.b64 _, [%4], 2048; }"
                     :: "r"(d + C_MX + (j * 8 + warp) * 4), "r"(__reduce_max_sync(~0u, mx)), "r"(d + MB_V), "r"(la), "r"(sb + MB_MR + gam * 8), "r"(w << 5) : "memory");
        const uint32_t lo = pack_bf16((cv[0] + cw[0]) * up, (cv[1] + cw[1]) * up), hi = pack_bf16((cv[2] + cw[2]) * up, (cv[3] + cw[3]) * up);
        st_async32(peer + 4096 + a, lo, peer + MB_V);
        st_async32(peer + 4096 + (a ^ 32), hi, peer + MB_V);
        st_async32(self + 4096 + a, lo, self + MB_V);
        st_async32(self + 4096 + (a ^ 32), hi, self + MB_V);
      }
      STAMP(6);
      if (s == NSEG - 1) break;
      const uint32_t wo_a = C_WO + (warp >> 1) * 16384 + ((la & 7) + ((la >> 4) << 3)) * 128 + ((((warp & 1) * 4 + ((la >> 3) & 1)) ^ (la & 7)) << 4);
#pragma unroll
      for (int u = 0; u < WO_EARLY; u++)
        ldm4t(Wo[u], sb + ((wo_a ^ ((u & 1) << 5)) | (u >= WO_PAR ? Wo[u - WO_PAR][0] & args.zero : 0u)) + ((u >> 1) << 11));
      if (s == 0) bar_sync<12, 384>();
      mbar_wait1(sb + MB_V, s & 1);
      E = max((int)(__reduce_max_sync(~0u, lds32(sb + C_MX + (la & 15) * 4)) >> 7) + E, (int)lds32(sb + C_XE + s * 4)) + (int)lds32(sb + C_WE);
      E = min(max(E, -100), 100);
      uint8_t* const rp = ring + (s & 7) * RING_SLOT + j * 16384 + (w >> 1) * 8192 + (gam ^ (w >> 1)) * 4096 + (w & 1) * 2048 + (la >> 4) * 1024;
      uint8_t* rp16 = rp + ((la >> 3) & 1) * 256 + (la & 7) * 16;
      uint8_t* rp4 = rp + 128 + ((la >> 1) & 7) * 4;
      uint32_t ot_ld = C_OT + (la ^ (((la >> 3) & 3) << 1)) * 16;
      uint32_t su_ld = C_SU + (la & 3) * 8;
      asm volatile("" : "+l"(rp16), "+l"(rp4), "+r"(ot_ld), "+r"(su_ld));
      bar_sync<7, 384>();
      STAMP2(3);
#pragma unroll
      for (int i = 0; i < 4; i++) ldm4t(b[i], sb + ot_ld + i * 512);
      const float2 su = lds64f(sb + su_ld);
#pragma unroll
      for (int u = WO_EARLY; u < 16; u++) ldm4t(Wo[u], sb + (wo_a ^ ((u & 1) << 5)) + ((u >> 1) << 11));
      mma16z(cq, Wo[0][0], Wo[0][1], Wo[0][2], Wo[0][3], b[0][0], b[0][1]);
      mma16z(ck, Wo[1][0], Wo[1][1], Wo[1][2], Wo[1][3], b[0][0], b[0][1]);
      mma16z(cv, Wo[2][0], Wo[2][1], Wo[2][2], Wo[2][3], b[0][2], b[0][3]);
      mma16z(cw, Wo[3][0], Wo[3][1], Wo[3][2], Wo[3][3], b[0][2], b[0][3]);
      const float dn = __uint_as_float((uint32_t)(127 - E) << 23);
      const float r0 = rcp(su.x) * dn, r1 = rcp(su.y) * dn;
#pragma unroll
      for (int k = 1; k < 4; k++) {
        mma16(cq, Wo[4 * k][0], Wo[4 * k][1], Wo[4 * k][2], Wo[4 * k][3], b[k][0], b[k][1]);
        mma16(ck, Wo[4 * k + 1][0], Wo[4 * k + 1][1], Wo[4 * k + 1][2], Wo[4 * k + 1][3], b[k][0], b[k][1]);
        mma16(cv, Wo[4 * k + 2][0], Wo[4 * k + 2][1], Wo[4 * k + 2][2], Wo[4 * k + 2][3], b[k][2], b[k][3]);
        mma16(cw, Wo[4 * k + 3][0], Wo[4 * k + 3][1], Wo[4 * k + 3][2], Wo[4 * k + 3][3], b[k][2], b[k][3]);
      }
      const int lb = fresh(lane);
      const uint32_t sel = (lb & 1) ? 0x5410 : 0x3210;
      {
        const uint32_t u0 = movm(pack_f16((cq[0] + cv[0]) * r0, (cq[1] + cv[1]) * r1)), u1 = movm(pack_f16((cq[2] + cv[2]) * r0, (cq[3] + cv[3]) * r1));
        const uint32_t u2 = movm(pack_f16((ck[0] + cw[0]) * r0, (ck[1] + cw[1]) * r1)), u3 = movm(pack_f16((ck[2] + cw[2]) * r0, (ck[3] + cw[3]) * r1));
        asm volatile("red.relaxed.gpu.global.add.noftz.v4.f16x2 [%0], {%1,%2,%3,%4};"
                     :: "l"(rp16), "r"(u0), "r"(u1), "r"(u2), "r"(__byte_perm(u3, 0x3C00u, sel)) : "memory");
        asm volatile("{ .reg .pred p; setp.eq.u32 p, %2, 0x5410; @p red.relaxed.gpu.global.add.noftz.f16x2 [%0], %1; }"
                     :: "l"(rp4), "r"(__byte_perm(u3, 0x3C00u, 0x5432)), "r"(sel) : "memory");
      }
      bar_arrive<9, 384>();
      STAMP(4);
      const uint32_t wv = w_off(lb);
#pragma unroll
      for (int i = 0; i < WV_A; i++) ldm4t(R[i], sb + C_WV + w_frag(wv | (i ? R[i - 1][0] & args.zero : 0u), i));
      {
        uint32_t z = R[WV_A - 1][3] & args.zero;
        for (int i = 0; i < delay; i++) z = __shfl_sync(~0u, z, 0);
        rp16 += z;
      }
      STAMP(5);
      uint4 a0;
      uint32_t b0;
      const uint32_t ev = (lb & 1) - 1u;
      mo = warp * 512 + lb * 16;
      int it = 0;
      do {
        a0 = ldv128(rp16);
        b0 = ldv32(rp4);
#pragma unroll
        for (int i = WV_A; i < 16; i++) ldm4t(R[i], sb + C_WV + w_frag(wv, i));
      } while (!__all_sync(~0u, (((a0.w | ev) & b0) >> 16) == 0x5000u || ++it >= 65536));
      pk[0] = f16_to_bf16(a0.x); pk[1] = f16_to_bf16(a0.y); pk[2] = f16_to_bf16(a0.z); pk[3] = f16_to_bf16(__byte_perm(a0.w, b0, sel));
      STAMP_NEXT;
    }
  } else {
    asm volatile("setmaxnreg.dec.sync.aligned.u32 " AUX_REGS ";");
    const int w = warp - 8, at = tid - 256;
    {
      if (at < 80) *reinterpret_cast<uint4*>(ring + (at / 10) * RING_SLOT + (cta >> 1) * 1024 + j * 256 + (at % 10) * 16) = make_uint4(0, 0, 0, 0);
      uint32_t mx = 0, mo = 0;
      const uint4 gw0 = __ldg(reinterpret_cast<const uint4*>(args.gate_w) + lane), gw1 = __ldg(reinterpret_cast<const uint4*>(args.gate_w) + 32 + lane);
#pragma unroll 2
      for (int r = 0; r < 8; r++) {
        const int tok = cta * SEGL + w * 8 + r;
        const uint4* xr = reinterpret_cast<const uint4*>(args.x + (size_t)tok * DM);
        const uint4 a = __ldg(xr + lane), b = __ldg(xr + 32 + lane);
        float acc = bf_lo(a.x) * bf_lo(gw0.x) + bf_hi(a.x) * bf_hi(gw0.x) + bf_lo(a.y) * bf_lo(gw0.y) + bf_hi(a.y) * bf_hi(gw0.y) +
                    bf_lo(a.z) * bf_lo(gw0.z) + bf_hi(a.z) * bf_hi(gw0.z) + bf_lo(a.w) * bf_lo(gw0.w) + bf_hi(a.w) * bf_hi(gw0.w) +
                    bf_lo(b.x) * bf_lo(gw1.x) + bf_hi(b.x) * bf_hi(gw1.x) + bf_lo(b.y) * bf_lo(gw1.y) + bf_hi(b.y) * bf_hi(gw1.y) +
                    bf_lo(b.z) * bf_lo(gw1.z) + bf_hi(b.z) * bf_hi(gw1.z) + bf_lo(b.w) * bf_lo(gw1.w) + bf_hi(b.w) * bf_hi(gw1.w);
        mx = absmax2(absmax2(mx, absmax2(absmax2(a.x, a.y), absmax2(a.z, a.w))), absmax2(absmax2(b.x, b.y), absmax2(b.z, b.w)));
#pragma unroll
        for (int o = 16; o; o >>= 1) acc += __shfl_xor_sync(~0u, acc, o);
        if (lane == 0) g_gate[tok] = __fdividef(1.0f, 1.0f + __expf(-acc));
      }
      const uint4* wr = reinterpret_cast<const uint4*>(args.wo + (size_t)(h * DH + w * 32) * DM + j * 256) + lane;
#pragma unroll 8
      for (int r = 0; r < 32; r++) {
        const uint4 a = __ldg(wr + r * (DM / 8));
        mo = absmax2(mo, absmax2(absmax2(a.x, a.y), absmax2(a.z, a.w)));
      }
      mx = __reduce_max_sync(~0u, fold_absmax(mx));
      mo = __reduce_max_sync(~0u, fold_absmax(mo));
      if (lane == 0) { sts32(sb + C_WM + 32 + w * 4, mx); sts32(sb + C_WM + 48 + w * 4, mo); }
      __threadfence();
    }
    bar_sync<10, 384>();
    if (at == 0) {
      mbar_expect_tx(sb + MB_WO, 65536);
      for (int i = 0; i < 4; i++) tma2d(sb + C_WO + i * 16384, &args.tmo, j * 256 + i * 64, h * DH, sb + MB_WO);
    }
    bar_sync<11, 384>();
    {
      if (at == 0) {
        const uint4 a = lds128(sb + C_WM), b = lds128(sb + C_WM + 16), c = lds128(sb + C_WM + 32), d = lds128(sb + C_WM + 48);
        uint4 r;
        r.x = tag;
        r.y = max(max(c.x, c.y), max(c.z, c.w)) >> 7;
        r.z = max(max(max(a.x, a.y), max(a.z, a.w)), max(max(b.x, b.y), max(b.z, b.w))) >> 7;
        r.w = max(max(d.x, d.y), max(d.z, d.w)) >> 7;
        asm volatile("st.volatile.global.v4.u32 [%0], {%1,%2,%3,%4};" :: "l"(&g_pub[cta]), "r"(r.x), "r"(r.y), "r"(r.z), "r"(r.w) : "memory");
      }
      if (w == 3) {
        uint4 r0, r1;
        int it = 0;
        while (true) {
          r0 = ldv128(&g_pub[lane]); r1 = ldv128(&g_pub[lane + 32]);
          if (__all_sync(~0u, r0.x == tag && r1.x == tag)) break;
          if (give_up(++it, 4)) break;
        }
        __threadfence();
        sts32(sb + C_XE + lane * 4, r0.y); sts32(sb + C_XE + 128 + lane * 4, r1.y);
        sts32(sb + C_WE, __reduce_max_sync(~0u, max(r0.z, r1.z)) + __reduce_max_sync(~0u, max(r0.w, r1.w)) - 3 * 126 + 21 - 14);
        for (int i = 0; i < 2; i++) {
          wait_count(g_fq + i * NH + h, tag * 4);
          asm volatile("fence.proxy.async.global;" ::: "memory");
          if (lane == 0) issue_stage(i, i);
        }
      }
      bar_arrive<12, 384>();
    }
    const uint32_t peer = mapa(sb, j ^ 1), self = mapa(sb, j);
    const float SC = 0.08838834764831845f * 1.4426950408889634f;
    const uint32_t ONE = 0x3F803F80u;
    int st = 0, stp = 0;
    const uint32_t l_row = (lane & 7) * 64 + (((lane >> 3) ^ ((lane & 7) >> 1)) << 4);
    const uint32_t l_km = (lane >> 3) * 128 + (((lane & 7) ^ ((lane >> 2) & 2)) << 4);
    for (int s = 0; s < NSEG; s++) {
      const uint32_t kv = C_KVQ + st * KVQ_ST + (j ? 0 : 4096), qx = C_KVQ + st * KVQ_ST + (j ? 16384 : 0);
      const uint32_t km = C_KM + (s & 1) * KM_BUF;
      uint32_t fq = 0;
      if (w == 3) fq = ld_relaxed(g_fq + min(s + 2, NSEG - 1) * NH + h + (lane & args.zero));
      const uint32_t l_v = ((fresh(l_row) ^ ((lane & 16) << 1)) | ((lane & 16) << 7)) + w * 512;
      mbar_wait1(sb + MB_KVQ + 8 * st, stp);
      if (s < NSEG - 1) {
        uint32_t kb[2][4], va[4][4], vm[2][4], q[4][4], kk[4];
        const uint32_t k_l = (l_row ^ ((w & 1) << 5)) + kv + w * 2048 + j * 1024;
        ldm4(kb[0], sb + k_l + (w >> 1) * 512); ldm4(kb[1], sb + k_l + 512 - (w >> 1) * 512);
        ldm4t(va[0], sb + kv + 8192 + l_v); ldm4t(va[1], sb + kv + 12288 + l_v); ldm4t(va[2], sb + kv + 8192 + (l_v ^ 32)); ldm4t(va[3], sb + kv + 12288 + (l_v ^ 32));
        const int lq = fresh(lane);
        uint32_t q_a = (((lq >> 3) * 128 + (((lq & 7) ^ ((lq >> 3) & 2)) << 4)) ^ ((w & 1) << 6)) + w * 512;
        uint32_t q_b = q_a ^ 576, q_c = q_a ^ 1024, q_d = q_a ^ 1600;
        uint32_t k_a = (l_km ^ ((w & 1) << 6)) + km + j * 2048 + w * 512;
        uint32_t sx = C_SX + lq * 16;
        asm volatile("" : "+r"(q_a), "+r"(q_b), "+r"(q_c), "+r"(q_d), "+r"(k_a), "+r"(sx));
        STAMP(13);
        bar_sync<6, 384>();
        STAMP2(8);
        {
          float s0[4], s1[4], s2[4], s3[4];
          ldm4t(q[0], sb + C_QM + q_a); ldm4t(q[1], sb + C_QM + q_b); ldm4t(kk, sb + k_a); ldm4t(q[2], sb + C_QM + q_c); ldm4t(q[3], sb + C_QM + q_d);
          mma16z(s0, q[0][0], q[0][1], q[0][2], q[0][3], kb[0][0], kb[0][1]);
          mma16z(s1, q[1][0], q[1][1], q[1][2], q[1][3], kb[0][2], kb[0][3]);
          mma16z(s2, q[0][0], q[0][1], q[0][2], q[0][3], kk[0], kk[1]);
          mma16z(s3, q[0][0], q[0][1], q[0][2], q[0][3], kk[2], kk[3]);
          mma16(s0, q[2][0], q[2][1], q[2][2], q[2][3], kb[1][0], kb[1][1]);
          mma16(s1, q[3][0], q[3][1], q[3][2], q[3][3], kb[1][2], kb[1][3]);
          const uint32_t x2 = __float_as_uint((s2[0] + s2[2]) + (s3[0] + s3[2])), x3 = __float_as_uint((s2[1] + s2[3]) + (s3[1] + s3[3]));
          const uint32_t x0 = __float_as_uint((s0[0] + s0[2]) + (s1[0] + s1[2])), x1 = __float_as_uint((s0[1] + s0[3]) + (s1[1] + s1[3]));
          st_async128(peer + 2048 + w * 512 + sx, x0, x1, x2, x3, peer + MB_S);
          st_async128(self + w * 512 + sx, x0, x1, x2, x3, self + MB_S);
        }
        STAMP(14);
        const int lc = fresh(lane);
        uint32_t ot_st = C_OT + (32 * w + 8 * ((lc & 7) >> 1) + ((2 * (lc >> 3)) ^ (lc & 6)) + (lc & 1)) * 16;
        uint32_t v_a = l_km + km + 4096 + w * 1024, v_b = (v_a ^ 64) + 512;
        asm volatile("" : "+r"(ot_st), "+r"(v_a), "+r"(v_b));
        mbar_wait1(sb + MB_S, s & 1);
        STAMP(9);
        float4 u[8];
#pragma unroll
        for (int i = 0; i < 8; i++) u[i] = lds128f(sb + sx + (i >> 1) * 512 + (i & 1) * 2048);
        mbar_wait1(sb + MB_V, s & 1);
        ldm4(vm[0], sb + v_a); ldm4(vm[1], sb + v_b);
        const float sv[10] = {u[0].x + u[1].x, u[0].y + u[1].y, u[2].x + u[3].x, u[2].y + u[3].y, u[4].x + u[5].x, u[4].y + u[5].y, u[6].x + u[7].x, u[6].y + u[7].y,
                              ((u[0].z + u[1].z) + (u[2].z + u[3].z)) + ((u[4].z + u[5].z) + (u[6].z + u[7].z)),
                              ((u[0].w + u[1].w) + (u[2].w + u[3].w)) + ((u[4].w + u[5].w) + (u[6].w + u[7].w))};
        float m = fmaxf(fmaxf(fmaxf(sv[0], sv[1]), fmaxf(sv[2], sv[3])), fmaxf(fmaxf(sv[4], sv[5]), fmaxf(sv[6], sv[7])));
        m = fmaxf(m, fmaxf(sv[8], sv[9]));
        m = fmaxf(fmaxf(m, __shfl_xor_sync(~0u, m, 1)), fmaxf(__shfl_xor_sync(~0u, m, 2), __shfl_xor_sync(~0u, m, 3)));
        m *= -SC;
        uint32_t p[5];
#pragma unroll
        for (int i = 0; i < 5; i++) p[i] = pack_bf16(ex2(fmaf(sv[2 * i], SC, m)), ex2(fmaf(sv[2 * i + 1], SC, m)));
        float o0[4], o1[4], su[4];
        mma16z(o0, va[0][0], va[0][1], va[0][2], va[0][3], p[0], p[1]);
        mma16z(o1, va[2][0], va[2][1], va[2][2], va[2][3], p[0], p[1]);
        mma16z(su, ONE, ONE, ONE, ONE, p[0], p[1]);
        mma16(o0, va[1][0], va[1][1], va[1][2], va[1][3], p[2], p[3]);
        mma16(o1, va[3][0], va[3][1], va[3][2], va[3][3], p[2], p[3]);
        mma16(su, ONE, ONE, ONE, ONE, p[2], p[3]);
        mma16(o0, vm[0][0], vm[0][1], vm[0][2], vm[0][3], p[4], p[4]);
        mma16(o1, vm[1][0], vm[1][1], vm[1][2], vm[1][3], p[4], p[4]);
        mma8(su, ONE, ONE, p[4]);
        stm4(sb + ot_st, pack_bf16(o0[0], o0[1]), pack_bf16(o0[2], o0[3]), pack_bf16(o1[0], o1[1]), pack_bf16(o1[2], o1[3]));
        asm volatile("{ .reg .pred p; setp.eq.u32 p, %3, %4; @p st.shared.v2.f32 [%0], {%1,%2}; }" :: "r"(sb + C_SU + w * 8), "f"(su[0]), "f"(su[1]), "r"(lc), "r"(w) : "memory");
        bar_arrive<7, 384>();
        STAMP(10);
      } else {
        bar_sync<6, 384>();
        mbar_wait1(sb + MB_V, s & 1);
      }
      if (w == 3) {
        if (lane == 0) {
          asm volatile("cp.async.bulk.wait_group 0;" ::: "memory");
          if (s > 0) FLAG_O(g_fo + 2 * (s - 1) + j);
          if (s + 2 < NSEG) {
            int it = 0;
            while ((int)(fq - tag * 4) < 0) { if (give_up(++it, 5)) break; fq = ld_acquire(g_fq + (s + 2) * NH + h); }
            asm volatile("fence.proxy.async.global;" ::: "memory");
            issue_stage(s + 2, st ? st - 1 : 2);
          }
        }
        __syncwarp();
      } else if (w == 0) {
        if (lane == 0 && s < NSEG - 1) { mbar_expect_tx(sb + MB_S, TX_S); mbar_expect_tx(sb + MB_V, TX_V); }
        __syncwarp();
      } else if (w == 1 && s >= 2) {
        if (lane < 10) asm volatile("st.global.v4.u32 [%0], {%1,%1,%1,%1};" :: "l"(ring + ((s - 2) & 7) * RING_SLOT + (cta >> 1) * 1024 + j * 256 + lane * 16), "r"(0) : "memory");
        __syncwarp();
      }
      {
        const int l = fresh(lane);
        const uint32_t q_l = (l & 7) * 64 + (((l >> 4) ^ ((l & 7) >> 1)) << 4) + ((l & 8) << 8) + w * 512;
        const uint32_t k_l = l_row + w * 512;
        const uint32_t k_a = l_km + km + w * 1024;
        float g0, g1;
        asm volatile("ld.global.cg.f32 %0, [%2]; ld.global.cg.f32 %1, [%2+32];" : "=f"(g0), "=f"(g1) : "l"(g_gate + s * SEGL + 16 * j + (l >> 2)) : "memory");
        if (s < NSEG - 1) bar_sync<9, 384>();
        STAMP2(11);
        float s0[4], s1[4], m0[4], m1[4];
#pragma unroll
        for (int i = 0; i < 4; i++) {
          uint32_t a[4], c[4], kb[4];
          ldm4(a, sb + qx + (q_l ^ (i * 512)));
          ldm4(kb, sb + kv + w * 2048 + (k_l ^ (i * 512)));
          ldm4(c, sb + qx + (q_l ^ (i * 512 + 32)));
          if (i == 0) {
            uint32_t k0[4], k1[4];
            ldm4t(k0, sb + k_a); ldm4t(k1, sb + (k_a ^ 64) + 512);
            mma16z(s0, a[0], a[1], a[2], a[3], kb[0], kb[1]); mma16z(s1, c[0], c[1], c[2], c[3], kb[2], kb[3]);
            mma16z(m0, a[0], a[1], a[2], a[3], k0[0], k0[1]); mma16z(m1, a[0], a[1], a[2], a[3], k0[2], k0[3]);
            mma16(m0, c[0], c[1], c[2], c[3], k1[0], k1[1]); mma16(m1, c[0], c[1], c[2], c[3], k1[2], k1[3]);
          } else {
            mma16(s0, a[0], a[1], a[2], a[3], kb[0], kb[1]); mma16(s1, c[0], c[1], c[2], c[3], kb[2], kb[3]);
          }
        }
        const float NEG = -1.0e9f * 1.4426950408889634f;
        const int d = 16 * j + (l >> 2) - 2 * (l & 3) - 8 * w;
        const uint32_t sa = sb + kv + l * 16;
        asm volatile("st.shared.v4.f32 [%0], {%1,%2,%3,%4};" :: "r"(sa + w * 2048), "f"(d >= 0 ? (s0[0] + s1[0]) * SC : NEG),
                     "f"(d >= 1 ? (s0[1] + s1[1]) * SC : NEG), "f"(d >= -8 ? (s0[2] + s1[2]) * SC : NEG), "f"(d >= -7 ? (s0[3] + s1[3]) * SC : NEG) : "memory");
        asm volatile("st.shared.v4.f32 [%0], {%1,%2,%3,%4};" :: "r"(sa + w * 2048 + 512), "f"((m0[0] + m1[0]) * SC), "f"((m0[1] + m1[1]) * SC),
                     "f"((m0[2] + m1[2]) * SC), "f"((m0[3] + m1[3]) * SC) : "memory");
        bar_sync<8, 128>();
        float4 sc[5];
        {
          const float4 u0 = lds128f(sa + 512), u1 = lds128f(sa + 2560), u2 = lds128f(sa + 4608), u3 = lds128f(sa + 6656);
#pragma unroll
          for (int i = 0; i < 4; i++) sc[i] = lds128f(sa + i * 2048);
          sc[4] = make_float4((u0.x + u1.x) + (u2.x + u3.x), (u0.y + u1.y) + (u2.y + u3.y), (u0.z + u1.z) + (u2.z + u3.z), (u0.w + u1.w) + (u2.w + u3.w));
        }
        uint32_t va[4][4], vm[2][4];
        ldm4t(va[0], sb + kv + 8192 + l_v); ldm4t(va[1], sb + kv + 12288 + l_v); ldm4t(va[2], sb + kv + 8192 + (l_v ^ 32)); ldm4t(va[3], sb + kv + 12288 + (l_v ^ 32));
        float x0 = fmaxf(sc[0].x, sc[0].y), x1 = fmaxf(sc[0].z, sc[0].w);
#pragma unroll
        for (int i = 1; i < 5; i++) { x0 = fmaxf(x0, fmaxf(sc[i].x, sc[i].y)); x1 = fmaxf(x1, fmaxf(sc[i].z, sc[i].w)); }
        x0 = fmaxf(x0, __shfl_xor_sync(~0u, x0, 1)); x1 = fmaxf(x1, __shfl_xor_sync(~0u, x1, 1));
        x0 = fmaxf(x0, __shfl_xor_sync(~0u, x0, 2)); x1 = fmaxf(x1, __shfl_xor_sync(~0u, x1, 2));
        uint32_t p[5][2];
#pragma unroll
        for (int i = 0; i < 5; i++) { p[i][0] = pack_bf16(ex2(sc[i].x - x0), ex2(sc[i].y - x0)); p[i][1] = pack_bf16(ex2(sc[i].z - x1), ex2(sc[i].w - x1)); }
        ldm4(vm[0], sb + k_a + 4096); ldm4(vm[1], sb + (k_a ^ 64) + 4608);
        float su[4], o[4][4];
        mma16z(su, p[0][0], p[0][1], p[1][0], p[1][1], ONE, ONE);
#pragma unroll
        for (int i = 0; i < 4; i++) mma16z(o[i], p[0][0], p[0][1], p[1][0], p[1][1], va[i & 2][i & 1], va[i & 2][(i & 1) + 2]);
        mma16(su, p[2][0], p[2][1], p[3][0], p[3][1], ONE, ONE);
#pragma unroll
        for (int i = 0; i < 4; i++) mma16(o[i], p[2][0], p[2][1], p[3][0], p[3][1], va[(i & 2) + 1][i & 1], va[(i & 2) + 1][(i & 1) + 2]);
        mma8(su, p[4][0], p[4][1], ONE);
#pragma unroll
        for (int i = 0; i < 4; i++) mma16(o[i], p[4][0], p[4][1], p[4][0], p[4][1], vm[i >> 1][i & 1], vm[i >> 1][(i & 1) + 2]);
        const float r0 = rcp(su[0]) * g0, r1 = rcp(su[2]) * g1;
        const uint32_t oa = sb + qx + w * 1024 + l * 16;
        sts128(oa, pack_bf16(o[0][0] * r0, o[0][1] * r0), pack_bf16(o[1][0] * r0, o[1][1] * r0), pack_bf16(o[2][0] * r0, o[2][1] * r0), pack_bf16(o[3][0] * r0, o[3][1] * r0));
        sts128(oa + 512, pack_bf16(o[0][2] * r1, o[0][3] * r1), pack_bf16(o[1][2] * r1, o[1][3] * r1), pack_bf16(o[2][2] * r1, o[2][3] * r1), pack_bf16(o[3][2] * r1, o[3][3] * r1));
        asm volatile("fence.proxy.async.shared::cta;" ::: "memory");
      }
      if (w == 3) {
        bar_sync<5, 128>();
        if (lane == 0) {
          asm volatile("cp.async.bulk.global.shared::cta.bulk_group [%0], [%1], 4096;" :: "l"(g_a + (size_t)(2 * s + j) * A_TILE + h * 4096), "r"(sb + qx) : "memory");
          asm volatile("cp.async.bulk.commit_group;" ::: "memory");
        }
        __syncwarp();
      } else {
        bar_arrive<5, 128>();
      }
      STAMP2(12);
      STAMP_NEXT;
      if (++st == 3) { st = 0; stp ^= 1; }
    }
    if (w == 3 && lane == 0) {
      asm volatile("cp.async.bulk.wait_group 0;" ::: "memory");
      FLAG_O(g_fo + 2 * (NSEG - 1) + j);
    }
    if (w == 0 && lane == 0) atomicAdd(&g_done, 1u);
  }
}

typedef CUresult (*EncodeFn)(CUtensorMap*, CUtensorMapDataType, cuuint32_t, void*, const cuuint64_t*, const cuuint64_t*, const cuuint32_t*,
                             const cuuint32_t*, CUtensorMapInterleave, CUtensorMapSwizzle, CUtensorMapL2promotion, CUtensorMapFloatOOBfill);
static void make_map(EncodeFn enc, CUtensorMap* tm, const void* base, uint64_t cols, uint64_t rows, uint32_t bc, uint32_t br) {
  cuuint64_t dims[2] = {cols, rows};
  cuuint64_t strides[1] = {cols * 2};
  cuuint32_t box[2] = {bc, br}, es[2] = {1, 1};
  enc(tm, CU_TENSOR_MAP_DATA_TYPE_BFLOAT16, 2, const_cast<void*>(base), dims, strides, box, es, CU_TENSOR_MAP_INTERLEAVE_NONE,
      CU_TENSOR_MAP_SWIZZLE_128B, CU_TENSOR_MAP_L2_PROMOTION_L2_256B, CU_TENSOR_MAP_FLOAT_OOB_FILL_NONE);
}

static int make_map5(EncodeFn enc, CUtensorMap* tm, const void* base, uint64_t cols, uint64_t rows, uint32_t groups, bool regroup) {
  const uint64_t rb = cols * 2;
  cuuint64_t dims[5] = {cols, 2, 4, 4, rows / 32};
  cuuint64_t strides[4] = {rb, (regroup ? 8 : 2) * rb, (regroup ? 2 : 8) * rb, 32 * rb};
  cuuint32_t box[5] = {64, 2, 4, 4, groups}, es[5] = {1, 1, 1, 1, 1};
  return (int)enc(tm, CU_TENSOR_MAP_DATA_TYPE_BFLOAT16, 5, const_cast<void*>(base), dims, strides, box, es, CU_TENSOR_MAP_INTERLEAVE_NONE,
                  CU_TENSOR_MAP_SWIZZLE_128B, CU_TENSOR_MAP_L2_PROMOTION_L2_256B, CU_TENSOR_MAP_FLOAT_OOB_FILL_NONE);
}

#define EST_STEP 4300.0
static void build_schedule(Args& a) {
  struct J { uint32_t code; int kind, p, n; double dur; bool done; };
  static J jobs[MAXJOBS];
  int nj = 0;
  const double KS = 1100.0, T0 = 12000.0, TQ = 115000.0;
  const int split[8] = {2, 2, 2, 2, 2, 2, 4, 16};
  for (int p = 0; p < 8; p++) for (int n = 0; n < 14; n++) jobs[nj++] = J{(uint32_t)(p << 1 | n << 4 | 8 << 15), 0, p, n, 8 * KS + 400, false};
  for (int p = 0; p < 8; p++) for (int n = 0; n < 2; n++)
    jobs[nj++] = J{(uint32_t)(1 | p << 1 | n << 4 | 64 << 8 | 28 << 15 | 1 << 22 | (split[p] + 1) << 23), 1, p, n, 28 * KS + 600, false};
  for (int p = 0; p < 8; p++) for (int q = 0; q < split[p]; q++) for (int n = 0; n < 2; n++) {
    const int nk = 64 / split[p];
    jobs[nj++] = J{(uint32_t)(1 | p << 1 | n << 4 | (q * nk) << 8 | nk << 15 | (split[p] + 1) << 23), 2, p, n, nk * KS + 1000, false};
  }
  double avail[NGC], hready[8] = {}, sready[16];
  int hleft[8]; bool sset[16] = {};
  static uint32_t lists[NGC][MAXJOBS]; int cnt[NGC] = {};
  for (int p = 0; p < 8; p++) hleft[p] = 14;
  for (int c = 0; c < NGC; c++) avail[c] = c < 32 ? TQ : 3000.0;
  for (int done = 0; done < nj; done++) {
    int c = 0;
    for (int i = 1; i < NGC; i++) if (avail[i] < avail[c]) c = i;
    int best = -1; double bt = 1e30;
    for (int i = 0; i < nj; i++) {
      J& q = jobs[i];
      if (q.done) continue;
      double r = 0;
      if (q.kind == 1) { if (hleft[q.p]) continue; r = hready[q.p]; }
      if (q.kind == 2) {
        if (!sset[q.p * 2 + q.n]) continue;
        r = T0 + (8 * q.p + 9) * EST_STEP;
        if (sready[q.p * 2 + q.n] - q.dur > r) r = sready[q.p * 2 + q.n] - q.dur;
      }
      if (r < avail[c]) r = avail[c];
      if (r < bt) { bt = r; best = i; }
    }
    J& q = jobs[best];
    q.done = true;
    avail[c] = bt + q.dur;
    lists[c][cnt[c]++] = q.code;
    if (q.kind == 0) { hleft[q.p]--; if (avail[c] > hready[q.p]) hready[q.p] = avail[c]; }
    if (q.kind == 1) { sset[q.p * 2 + q.n] = true; sready[q.p * 2 + q.n] = avail[c]; }
  }
  int o = 0;
  for (int c = 0; c < NGC; c++) { a.first[c] = (uint16_t)o; for (int i = 0; i < cnt[c]; i++) a.job[o++] = lists[c][i]; }
  a.first[NGC] = (uint16_t)o; a.first[NGC + 1] = 0; a.zero = 0;
  for (; o < MAXJOBS; o++) a.job[o] = 0;
}

extern "C" void kernel_launch(void* const* d_in, const int* in_sizes, int n_in, void* d_out, int out_size) {
  (void)in_sizes; (void)n_in; (void)out_size;
  const bf16 *wq = (const bf16*)d_in[2], *wk = (const bf16*)d_in[3], *wv = (const bf16*)d_in[4], *wo = (const bf16*)d_in[5],
             *wg = (const bf16*)d_in[8], *wu = (const bf16*)d_in[9], *wd = (const bf16*)d_in[10];
  static EncodeFn enc = nullptr;
  static Args a;
  if (!enc) {
    void* fn = nullptr; cudaDriverEntryPointQueryResult qr;
    cudaGetDriverEntryPoint("cuTensorMapEncodeTiled", &fn, cudaEnableDefault, &qr);
    enc = (EncodeFn)fn;
    cudaFuncSetAttribute(fused_kernel, cudaFuncAttributeMaxDynamicSharedMemorySize, K_SMEM);
    build_schedule(a);
  }
  make_map(enc, &a.tmq, wq, HD, DM, 64, 256); make_map(enc, &a.tmk, wk, HD, DM, 64, 256); make_map(enc, &a.tmv, wv, HD, DM, 64, 256);
  make_map(enc, &a.tmo, wo, DM, HD, 64, 128);
  int rc = make_map5(enc, &a.pw[0], wk, HD, DM, 4, true) | make_map5(enc, &a.pw[1], wv, HD, DM, 4, true) | make_map5(enc, &a.pw[2], wq, HD, DM, 4, true) |
           make_map5(enc, &a.pb[0], wg, FF, DM, 2, true) | make_map5(enc, &a.pb[1], wu, FF, DM, 2, true) |
           make_map5(enc, &a.pb[2], wo, DM, HD, 2, true) | make_map5(enc, &a.pb[3], wd, DM, FF, 2, false);
  if (rc) return;
  a.x = (const bf16*)d_in[0]; a.mem0 = (const bf16*)d_in[1]; a.wo = wo; a.gate_w = (const bf16*)d_in[11]; a.out = (bf16*)d_out;
  cudaLaunchConfig_t cfg = {};
  cfg.gridDim = dim3(NCTA); cfg.blockDim = dim3(384); cfg.dynamicSmemBytes = K_SMEM; cfg.stream = cudaStreamPerThread;
  cudaLaunchAttribute at[1];
  at[0].id = cudaLaunchAttributeClusterDimension; at[0].val.clusterDim.x = 2; at[0].val.clusterDim.y = 1; at[0].val.clusterDim.z = 1;
  cfg.attrs = at; cfg.numAttrs = 1;
  cudaLaunchKernelEx(&cfg, fused_kernel, a);
}
```

```cpp
#include <cuda_runtime.h>
#include <cuda_bf16.h>
#include <cuda_fp16.h>
#include <cuda.h>
#include <stdint.h>

typedef __nv_bfloat16 bf16;
#define FAT_REGS "216"
#define AUX_REGS "72"
#define WO_QK 6
#define WO_AT 5
#define WO_EARLY 16
#define WO_PAR 2
#define WV_A 10
#define FLAG_O red_relaxed
#define GLU_EARLY 12
#define POLL_DELAY 2

constexpr int SEQ = 2048, DM = 512, NH = 32, DH = 128, SEGL = 32, NSEG = 64, FF = 1792;
constexpr int HD = NH * DH;
constexpr int KA = HD + FF;
constexpr int NCTA = 132, NGC = 34, MAXJOBS = 320;
constexpr int BLK_BYTES = 24576;
constexpr int RING_SLOT = 32768;
constexpr int A_TILE = KA / 32 * 1024;
constexpr int SPIN_LIMIT = 1 << 20;

__device__ __align__(1024) uint8_t g_qkv[(size_t)NSEG * NH * BLK_BYTES];
__device__ __align__(1024) uint8_t g_a[(size_t)SEQ * KA * 2];
__device__ __align__(1024) float g_acc[(size_t)SEQ * DM];
__device__ unsigned g_fq[NSEG * NH];
__device__ unsigned g_fh[128];
__device__ unsigned g_fo[128];
__device__ unsigned g_fc[256];
__device__ __align__(1024) uint8_t g_ring[16 * RING_SLOT];
__device__ __align__(128) float g_gate[SEQ];
__device__ uint4 g_pub[64];
__device__ unsigned g_done;
__device__ int g_err;

__device__ __forceinline__ uint32_t smem_u32(const void* p) { return (uint32_t)__cvta_generic_to_shared(p); }
__device__ __forceinline__ uint32_t mapa(uint32_t a, uint32_t rank) { uint32_t r; asm volatile("mapa.shared::cluster.u32 %0, %1, %2;" : "=r"(r) : "r"(a), "r"(rank)); return r; }
__device__ __forceinline__ void mbar_init(uint32_t a, uint32_t cnt) { asm volatile("mbarrier.init.shared::cta.b64 [%0], %1;" :: "r"(a), "r"(cnt) : "memory"); }
__device__ __forceinline__ void mbar_expect_tx(uint32_t a, uint32_t bytes) { asm volatile("mbarrier.arrive.expect_tx.shared::cta.b64 _, [%0], %1;" :: "r"(a), "r"(bytes) : "memory"); }
__device__ __forceinline__ bool mbar_try(uint32_t a, uint32_t parity) {
  uint32_t ok;
  asm volatile("{ .reg .pred p; mbarrier.try_wait.parity.shared::cta.b64 p, [%1], %2; selp.u32 %0, 1, 0, p; }" : "=r"(ok) : "r"(a), "r"(parity) : "memory");
  return ok;
}
__device__ __forceinline__ bool mbar_try_cluster(uint32_t a, uint32_t parity) {
  uint32_t ok;
  asm volatile("{ .reg .pred p; mbarrier.try_wait.parity.acquire.cluster.shared::cta.b64 p, [%1], %2; selp.u32 %0, 1, 0, p; }" : "=r"(ok) : "r"(a), "r"(parity) : "memory");
  return ok;
}
__device__ __forceinline__ bool give_up(int it, int code) {
  if ((it & 1023) != 0) return false;
  if (it < SPIN_LIMIT && *reinterpret_cast<volatile int*>(&g_err) == 0) return false;
  if (it >= SPIN_LIMIT) g_err = code;
  return true;
}
__device__ __forceinline__ void mbar_wait(uint32_t a, uint32_t parity) {
  int it = 0;
  while (!mbar_try(a, parity)) { if (give_up(++it, 1)) break; }
}
__device__ __forceinline__ void mbar_wait1(uint32_t a, uint32_t parity) {
  asm volatile("{ .reg .pred p; .reg .u32 c; mov.u32 c, 0;\nW: mbarrier.try_wait.parity.shared::cta.b64 p, [%0], %1;\n"
               "add.u32 c, c, 1; setp.lt.and.u32 p, c, 65536, !p; @p bra W; }" :: "r"(a), "r"(parity) : "memory");
}
__device__ __forceinline__ void mbar_wait_cluster(uint32_t a, uint32_t parity) {
  int it = 0;
  while (!mbar_try_cluster(a, parity)) { if (give_up(++it, 2)) break; }
}
template <int ID, int N> __device__ __forceinline__ void bar_sync() { asm volatile("bar.sync %0, %1;" :: "n"(ID), "n"(N) : "memory"); }
template <int ID, int N> __device__ __forceinline__ void bar_arrive() { asm volatile("bar.arrive %0, %1;" :: "n"(ID), "n"(N) : "memory"); }
__device__ __forceinline__ void bar_sync_id(int id, int n) { asm volatile("bar.sync %0, %1;" :: "r"(id), "r"(n) : "memory"); }
__device__ __forceinline__ void tma2d(uint32_t dst, const CUtensorMap* tm, int c0, int c1, uint32_t mb) {
  asm volatile("cp.async.bulk.tensor.2d.shared::cluster.global.mbarrier::complete_tx::bytes [%0], [%1, {%3, %4}], [%2];"
               :: "r"(dst), "l"((uint64_t)tm), "r"(mb), "r"(c0), "r"(c1) : "memory");
}
__device__ __forceinline__ void bulk_g2s(uint32_t dst, const void* src, uint32_t bytes, uint32_t mb) {
  asm volatile("cp.async.bulk.shared::cluster.global.mbarrier::complete_tx::bytes [%0], [%1], %2, [%3];"
               :: "r"(dst), "l"(src), "r"(bytes), "r"(mb) : "memory");
}
__device__ __forceinline__ void ldm4(uint32_t* r, uint32_t a) {
  asm volatile("ldmatrix.sync.aligned.m8n8.x4.shared.b16 {%0,%1,%2,%3}, [%4];" : "=r"(r[0]), "=r"(r[1]), "=r"(r[2]), "=r"(r[3]) : "r"(a) : "memory");
}
__device__ __forceinline__ void ldm4t(uint32_t* r, uint32_t a) {
  asm volatile("ldmatrix.sync.aligned.m8n8.x4.trans.shared.b16 {%0,%1,%2,%3}, [%4];" : "=r"(r[0]), "=r"(r[1]), "=r"(r[2]), "=r"(r[3]) : "r"(a) : "memory");
}
__device__ __forceinline__ void stm4(uint32_t a, uint32_t r0, uint32_t r1, uint32_t r2, uint32_t r3) {
  asm volatile("stmatrix.sync.aligned.m8n8.x4.shared.b16 [%0], {%1,%2,%3,%4};" :: "r"(a), "r"(r0), "r"(r1), "r"(r2), "r"(r3) : "memory");
}
__device__ __forceinline__ void stm4t(uint32_t a, uint32_t r0, uint32_t r1, uint32_t r2, uint32_t r3) {
  asm volatile("stmatrix.sync.aligned.m8n8.x4.trans.shared.b16 [%0], {%1,%2,%3,%4};" :: "r"(a), "r"(r0), "r"(r1), "r"(r2), "r"(r3) : "memory");
}
__device__ __forceinline__ void hma16(float* d, const uint32_t* a, uint32_t b0, uint32_t b1) {
  asm volatile("mma.sync.aligned.m16n8k16.row.col.f32.f16.f16.f32 {%0,%1,%2,%3}, {%4,%5,%6,%7}, {%8,%9}, {%0,%1,%2,%3};"
               : "+f"(d[0]), "+f"(d[1]), "+f"(d[2]), "+f"(d[3]) : "r"(a[0]), "r"(a[1]), "r"(a[2]), "r"(a[3]), "r"(b0), "r"(b1));
}
__device__ __forceinline__ void hma16z(float* d, const uint32_t* a, uint32_t b0, uint32_t b1) {
  asm volatile("mma.sync.aligned.m16n8k16.row.col.f32.f16.f16.f32 {%0,%1,%2,%3}, {%4,%5,%6,%7}, {%8,%9}, {%10,%10,%10,%10};"
               : "=f"(d[0]), "=f"(d[1]), "=f"(d[2]), "=f"(d[3]) : "r"(a[0]), "r"(a[1]), "r"(a[2]), "r"(a[3]), "r"(b0), "r"(b1), "f"(0.f));
}
__device__ __forceinline__ void mma16(float* d, uint32_t a0, uint32_t a1, uint32_t a2, uint32_t a3, uint32_t b0, uint32_t b1) {
  asm volatile("mma.sync.aligned.m16n8k16.row.col.f32.bf16.bf16.f32 {%0,%1,%2,%3}, {%4,%5,%6,%7}, {%8,%9}, {%0,%1,%2,%3};"
               : "+f"(d[0]), "+f"(d[1]), "+f"(d[2]), "+f"(d[3]) : "r"(a0), "r"(a1), "r"(a2), "r"(a3), "r"(b0), "r"(b1));
}
__device__ __forceinline__ void mma16z(float* d, uint32_t a0, uint32_t a1, uint32_t a2, uint32_t a3, uint32_t b0, uint32_t b1) {
  asm volatile("mma.sync.aligned.m16n8k16.row.col.f32.bf16.bf16.f32 {%0,%1,%2,%3}, {%4,%5,%6,%7}, {%8,%9}, {%10,%10,%10,%10};"
               : "=f"(d[0]), "=f"(d[1]), "=f"(d[2]), "=f"(d[3]) : "r"(a0), "r"(a1), "r"(a2), "r"(a3), "r"(b0), "r"(b1), "f"(0.f));
}
__device__ __forceinline__ void mma8(float* d, uint32_t a0, uint32_t a1, uint32_t b0) {
  asm volatile("mma.sync.aligned.m16n8k8.row.col.f32.bf16.bf16.f32 {%0,%1,%2,%3}, {%4,%5}, {%6}, {%0,%1,%2,%3};"
               : "+f"(d[0]), "+f"(d[1]), "+f"(d[2]), "+f"(d[3]) : "r"(a0), "r"(a1), "r"(b0));
}
__device__ __forceinline__ void mma8z(float* d, uint32_t a0, uint32_t a1, uint32_t b0) {
  asm volatile("mma.sync.aligned.m16n8k8.row.col.f32.bf16.bf16.f32 {%0,%1,%2,%3}, {%4,%5}, {%6}, {%7,%7,%7,%7};"
               : "=f"(d[0]), "=f"(d[1]), "=f"(d[2]), "=f"(d[3]) : "r"(a0), "r"(a1), "r"(b0), "f"(0.f));
}
__device__ __forceinline__ uint32_t pack_bf16(float lo, float hi) { uint32_t r; asm("cvt.rn.bf16x2.f32 %0, %1, %2;" : "=r"(r) : "f"(hi), "f"(lo)); return r; }
__device__ __forceinline__ uint32_t pack_f16(float lo, float hi) { uint32_t r; asm("cvt.rn.f16x2.f32 %0, %1, %2;" : "=r"(r) : "f"(hi), "f"(lo)); return r; }
__device__ __forceinline__ float2 unpack_f16(uint32_t v) { return __half22float2(*reinterpret_cast<__half2*>(&v)); }
__device__ __forceinline__ uint32_t absmax2(uint32_t a, uint32_t b) { uint32_t r; asm("max.xorsign.abs.bf16x2 %0, %1, %2;" : "=r"(r) : "r"(a), "r"(b)); return r; }
__device__ __forceinline__ uint32_t absmax2h(uint32_t a, uint32_t b) { uint32_t r; asm("max.xorsign.abs.f16x2 %0, %1, %2;" : "=r"(r) : "r"(a), "r"(b)); return r; }
__device__ __forceinline__ uint32_t hadd2(uint32_t a, uint32_t b) { uint32_t r; asm("add.rn.bf16x2 %0, %1, %2;" : "=r"(r) : "r"(a), "r"(b)); return r; }
__device__ __forceinline__ void sts64(uint32_t a, uint32_t x, uint32_t y) { asm volatile("st.shared.v2.u32 [%0], {%1,%2};" :: "r"(a), "r"(x), "r"(y) : "memory"); }
__device__ __forceinline__ uint2 lds64(uint32_t a) { uint2 v; asm volatile("ld.shared.v2.u32 {%0,%1}, [%2];" : "=r"(v.x), "=r"(v.y) : "r"(a) : "memory"); return v; }
__device__ __forceinline__ void lds64r(uint32_t* r, uint32_t a) { asm volatile("ld.shared.v2.u32 {%0,%1}, [%2];" : "=r"(r[0]), "=r"(r[1]) : "r"(a) : "memory"); }
__device__ __forceinline__ void ldv_s(uint32_t* r, uint32_t a) {
  asm volatile("ld.volatile.shared.v4.u32 {%0,%1,%2,%3}, [%4];" : "=r"(r[0]), "=r"(r[1]), "=r"(r[2]), "=r"(r[3]) : "r"(a) : "memory");
}
__device__ __forceinline__ float ex2v(float x) { float r; asm volatile("ex2.approx.ftz.f32 %0, %1;" : "=f"(r) : "f"(x)); return r; }
__device__ __forceinline__ uint32_t fold_absmax(uint32_t m) { m &= 0x7FFF7FFFu; return max(m & 0xFFFFu, m >> 16); }
__device__ __forceinline__ float ex2(float x) { float r; asm("ex2.approx.ftz.f32 %0, %1;" : "=f"(r) : "f"(x)); return r; }
__device__ __forceinline__ void sts32(uint32_t a, uint32_t v) { asm volatile("st.shared.u32 [%0], %1;" :: "r"(a), "r"(v) : "memory"); }
__device__ __forceinline__ void sts64f(uint32_t a, float x, float y) { asm volatile("st.shared.v2.f32 [%0], {%1,%2};" :: "r"(a), "f"(x), "f"(y) : "memory"); }
__device__ __forceinline__ float2 lds64f(uint32_t a) { float2 v; asm volatile("ld.shared.v2.f32 {%0,%1}, [%2];" : "=f"(v.x), "=f"(v.y) : "r"(a) : "memory"); return v; }
__device__ __forceinline__ uint32_t lds32(uint32_t a) { uint32_t v; asm volatile("ld.shared.u32 %0, [%1];" : "=r"(v) : "r"(a) : "memory"); return v; }
__device__ __forceinline__ uint4 lds128(uint32_t a) { uint4 v; asm volatile("ld.shared.v4.u32 {%0,%1,%2,%3}, [%4];" : "=r"(v.x), "=r"(v.y), "=r"(v.z), "=r"(v.w) : "r"(a) : "memory"); return v; }
__device__ __forceinline__ void st_async32(uint32_t a, uint32_t v, uint32_t mb) {
  asm volatile("st.async.weak.shared::cluster.mbarrier::complete_tx::bytes.b32 [%0], %1, [%2];" :: "r"(a), "r"(v), "r"(mb) : "memory");
}
__device__ __forceinline__ void st_async64(uint32_t a, uint32_t x, uint32_t y, uint32_t mb) {
  asm volatile("st.async.weak.shared::cluster.mbarrier::complete_tx::bytes.v2.b32 [%0], {%1,%2}, [%3];" :: "r"(a), "r"(x), "r"(y), "r"(mb) : "memory");
}
__device__ __forceinline__ void st_async128(uint32_t a, uint32_t x, uint32_t y, uint32_t z, uint32_t w, uint32_t mb) {
  asm volatile("st.async.weak.shared::cluster.mbarrier::complete_tx::bytes.v4.b32 [%0], {%1,%2,%3,%4}, [%5];" :: "r"(a), "r"(x), "r"(y), "r"(z), "r"(w), "r"(mb) : "memory");
}
__device__ __forceinline__ void sts128(uint32_t a, uint32_t x, uint32_t y, uint32_t z, uint32_t w) {
  asm volatile("st.shared.v4.u32 [%0], {%1,%2,%3,%4};" :: "r"(a), "r"(x), "r"(y), "r"(z), "r"(w) : "memory");
}
__device__ __forceinline__ void lds128r(uint32_t* r, uint32_t a) {
  asm volatile("ld.shared.v4.u32 {%0,%1,%2,%3}, [%4];" : "=r"(r[0]), "=r"(r[1]), "=r"(r[2]), "=r"(r[3]) : "r"(a) : "memory");
}
__device__ __forceinline__ float4 lds128f(uint32_t a) { float4 v; asm volatile("ld.shared.v4.f32 {%0,%1,%2,%3}, [%4];" : "=f"(v.x), "=f"(v.y), "=f"(v.z), "=f"(v.w) : "r"(a) : "memory"); return v; }
__device__ __forceinline__ void mbar_arrive(uint32_t a) { asm volatile("mbarrier.arrive.shared::cta.b64 _, [%0];" :: "r"(a) : "memory"); }
__device__ __forceinline__ uint32_t movm(uint32_t a) { uint32_t d; asm volatile("movmatrix.sync.aligned.m8n8.trans.b16 %0, %1;" : "=r"(d) : "r"(a)); return d; }
__device__ __forceinline__ float rcp(float x) { float r; asm("rcp.approx.ftz.f32 %0, %1;" : "=f"(r) : "f"(x)); return r; }
__device__ __forceinline__ uint32_t f16_to_bf16(uint32_t v) { const float2 f = unpack_f16(v); return pack_bf16(f.x, f.y); }
__device__ __forceinline__ uint4 ldv128(const void* p) {
  uint4 v; asm volatile("ld.volatile.global.v4.u32 {%0,%1,%2,%3}, [%4];" : "=r"(v.x), "=r"(v.y), "=r"(v.z), "=r"(v.w) : "l"(p) : "memory"); return v;
}
__device__ __forceinline__ uint32_t ldv32(const void* p) { uint32_t v; asm volatile("ld.volatile.global.u32 %0, [%1];" : "=r"(v) : "l"(p) : "memory"); return v; }
__device__ __forceinline__ float bf_lo(uint32_t v) { return __uint_as_float(v << 16); }
__device__ __forceinline__ float bf_hi(uint32_t v) { return __uint_as_float(v & 0xFFFF0000u); }

__device__ __forceinline__ void wgmma_rs192(float* d, uint32_t a0, uint32_t a1, uint32_t a2, uint32_t a3, uint64_t desc, int acc) {
  asm volatile("{ .reg .pred p; setp.ne.b32 p, %101, 0;\n"
    "wgmma.mma_async.sync.aligned.m64n192k16.f32.bf16.bf16 {%0,%1,%2,%3,%4,%5,%6,%7,%8,%9,%10,%11,%12,%13,%14,%15,%16,%17,%18,%19,%20,%21,%22,%23,%24,%25,%26,%27,%28,%29,%30,%31,%32,%33,%34,%35,%36,%37,%38,%39,%40,%41,%42,%43,%44,%45,%46,%47,%48,%49,%50,%51,%52,%53,%54,%55,%56,%57,%58,%59,%60,%61,%62,%63,%64,%65,%66,%67,%68,%69,%70,%71,%72,%73,%74,%75,%76,%77,%78,%79,%80,%81,%82,%83,%84,%85,%86,%87,%88,%89,%90,%91,%92,%93,%94,%95}, {%96,%97,%98,%99}, %100, p, 1, 1, 1; }"
    :
      "+f"(d[0]), "+f"(d[1]), "+f"(d[2]), "+f"(d[3]), "+f"(d[4]), "+f"(d[5]), "+f"(d[6]), "+f"(d[7]), "+f"(d[8]), "+f"(d[9]), "+f"(d[10]), "+f"(d[11]),
      "+f"(d[12]), "+f"(d[13]), "+f"(d[14]), "+f"(d[15]), "+f"(d[16]), "+f"(d[17]), "+f"(d[18]), "+f"(d[19]), "+f"(d[20]), "+f"(d[21]), "+f"(d[22]), "+f"(d[23]),
      "+f"(d[24]), "+f"(d[25]), "+f"(d[26]), "+f"(d[27]), "+f"(d[28]), "+f"(d[29]), "+f"(d[30]), "+f"(d[31]), "+f"(d[32]), "+f"(d[33]), "+f"(d[34]), "+f"(d[35]),
      "+f"(d[36]), "+f"(d[37]), "+f"(d[38]), "+f"(d[39]), "+f"(d[40]), "+f"(d[41]), "+f"(d[42]), "+f"(d[43]), "+f"(d[44]), "+f"(d[45]), "+f"(d[46]), "+f"(d[47]),
      "+f"(d[48]), "+f"(d[49]), "+f"(d[50]), "+f"(d[51]), "+f"(d[52]), "+f"(d[53]), "+f"(d[54]), "+f"(d[55]), "+f"(d[56]), "+f"(d[57]), "+f"(d[58]), "+f"(d[59]),
      "+f"(d[60]), "+f"(d[61]), "+f"(d[62]), "+f"(d[63]), "+f"(d[64]), "+f"(d[65]), "+f"(d[66]), "+f"(d[67]), "+f"(d[68]), "+f"(d[69]), "+f"(d[70]), "+f"(d[71]),
      "+f"(d[72]), "+f"(d[73]), "+f"(d[74]), "+f"(d[75]), "+f"(d[76]), "+f"(d[77]), "+f"(d[78]), "+f"(d[79]), "+f"(d[80]), "+f"(d[81]), "+f"(d[82]), "+f"(d[83]),
      "+f"(d[84]), "+f"(d[85]), "+f"(d[86]), "+f"(d[87]), "+f"(d[88]), "+f"(d[89]), "+f"(d[90]), "+f"(d[91]), "+f"(d[92]), "+f"(d[93]), "+f"(d[94]), "+f"(d[95])
    : "r"(a0), "r"(a1), "r"(a2), "r"(a3), "l"(desc), "r"(acc));
}

__device__ __forceinline__ void wgmma_rs256(float* d, uint32_t a0, uint32_t a1, uint32_t a2, uint32_t a3, uint64_t desc, int acc) {
  asm volatile("{ .reg .pred p; setp.ne.b32 p, %133, 0;\n"
    "wgmma.mma_async.sync.aligned.m64n256k16.f32.bf16.bf16 {%0,%1,%2,%3,%4,%5,%6,%7,%8,%9,%10,%11,%12,%13,%14,%15,%16,%17,%18,%19,%20,%21,%22,%23,%24,%25,%26,%27,%28,%29,%30,%31,%32,%33,%34,%35,%36,%37,%38,%39,%40,%41,%42,%43,%44,%45,%46,%47,%48,%49,%50,%51,%52,%53,%54,%55,%56,%57,%58,%59,%60,%61,%62,%63,%64,%65,%66,%67,%68,%69,%70,%71,%72,%73,%74,%75,%76,%77,%78,%79,%80,%81,%82,%83,%84,%85,%86,%87,%88,%89,%90,%91,%92,%93,%94,%95,%96,%97,%98,%99,%100,%101,%102,%103,%104,%105,%106,%107,%108,%109,%110,%111,%112,%113,%114,%115,%116,%117,%118,%119,%120,%121,%122,%123,%124,%125,%126,%127}, {%128,%129,%130,%131}, %132, p, 1, 1, 1; }"
    :
      "+f"(d[0]), "+f"(d[1]), "+f"(d[2]), "+f"(d[3]), "+f"(d[4]), "+f"(d[5]), "+f"(d[6]), "+f"(d[7]), "+f"(d[8]), "+f"(d[9]), "+f"(d[10]), "+f"(d[11]),
      "+f"(d[12]), "+f"(d[13]), "+f"(d[14]), "+f"(d[15]), "+f"(d[16]), "+f"(d[17]), "+f"(d[18]), "+f"(d[19]), "+f"(d[20]), "+f"(d[21]), "+f"(d[22]), "+f"(d[23]),
      "+f"(d[24]), "+f"(d[25]), "+f"(d[26]), "+f"(d[27]), "+f"(d[28]), "+f"(d[29]), "+f"(d[30]), "+f"(d[31]), "+f"(d[32]), "+f"(d[33]), "+f"(d[34]), "+f"(d[35]),
      "+f"(d[36]), "+f"(d[37]), "+f"(d[38]), "+f"(d[39]), "+f"(d[40]), "+f"(d[41]), "+f"(d[42]), "+f"(d[43]), "+f"(d[44]), "+f"(d[45]), "+f"(d[46]), "+f"(d[47]),
      "+f"(d[48]), "+f"(d[49]), "+f"(d[50]), "+f"(d[51]), "+f"(d[52]), "+f"(d[53]), "+f"(d[54]), "+f"(d[55]), "+f"(d[56]), "+f"(d[57]), "+f"(d[58]), "+f"(d[59]),
      "+f"(d[60]), "+f"(d[61]), "+f"(d[62]), "+f"(d[63]), "+f"(d[64]), "+f"(d[65]), "+f"(d[66]), "+f"(d[67]), "+f"(d[68]), "+f"(d[69]), "+f"(d[70]), "+f"(d[71]),
      "+f"(d[72]), "+f"(d[73]), "+f"(d[74]), "+f"(d[75]), "+f"(d[76]), "+f"(d[77]), "+f"(d[78]), "+f"(d[79]), "+f"(d[80]), "+f"(d[81]), "+f"(d[82]), "+f"(d[83]),
      "+f"(d[84]), "+f"(d[85]), "+f"(d[86]), "+f"(d[87]), "+f"(d[88]), "+f"(d[89]), "+f"(d[90]), "+f"(d[91]), "+f"(d[92]), "+f"(d[93]), "+f"(d[94]), "+f"(d[95]),
      "+f"(d[96]), "+f"(d[97]), "+f"(d[98]), "+f"(d[99]), "+f"(d[100]), "+f"(d[101]), "+f"(d[102]), "+f"(d[103]), "+f"(d[104]), "+f"(d[105]), "+f"(d[106]), "+f"(d[107]),
      "+f"(d[108]), "+f"(d[109]), "+f"(d[110]), "+f"(d[111]), "+f"(d[112]), "+f"(d[113]), "+f"(d[114]), "+f"(d[115]), "+f"(d[116]), "+f"(d[117]), "+f"(d[118]), "+f"(d[119]),
      "+f"(d[120]), "+f"(d[121]), "+f"(d[122]), "+f"(d[123]), "+f"(d[124]), "+f"(d[125]), "+f"(d[126]), "+f"(d[127])
    : "r"(a0), "r"(a1), "r"(a2), "r"(a3), "l"(desc), "r"(acc));
}

__device__ __forceinline__ void wg_fence() { asm volatile("wgmma.fence.sync.aligned;" ::: "memory"); }
__device__ __forceinline__ void wg_commit() { asm volatile("wgmma.commit_group.sync.aligned;" ::: "memory"); }
template <int N> __device__ __forceinline__ void wg_wait() { asm volatile("wgmma.wait_group.sync.aligned %0;" :: "n"(N) : "memory"); }
__device__ __forceinline__ void tma5d(uint32_t dst, const CUtensorMap* tm, int c0, int c4, uint32_t mb) {
  asm volatile("cp.async.bulk.tensor.5d.shared::cluster.global.mbarrier::complete_tx::bytes [%0], [%1, {%3, %5, %5, %5, %4}], [%2];"
               :: "r"(dst), "l"((uint64_t)tm), "r"(mb), "r"(c0), "r"(c4), "r"(0) : "memory");
}
__device__ __forceinline__ void tma5d_mc(uint32_t dst, const CUtensorMap* tm, int c0, int c4, uint32_t mb) {
  asm volatile("cp.async.bulk.tensor.5d.shared::cluster.global.mbarrier::complete_tx::bytes.multicast::cluster [%0], [%1, {%3, %5, %5, %5, %4}], [%2], %6;"
               :: "r"(dst), "l"((uint64_t)tm), "r"(mb), "r"(c0), "r"(c4), "r"(0), "h"((unsigned short)3) : "memory");
}
__device__ __forceinline__ void mbar_arrive_cluster(uint32_t a) { asm volatile("mbarrier.arrive.shared::cluster.b64 _, [%0];" :: "r"(a) : "memory"); }
__device__ __forceinline__ void ldg128(uint32_t* r, const uint8_t* p) {
  asm volatile("ld.global.L1::no_allocate.v4.u32 {%0,%1,%2,%3}, [%4];" : "=r"(r[0]), "=r"(r[1]), "=r"(r[2]), "=r"(r[3]) : "l"(p) : "memory");
}
__device__ __forceinline__ uint32_t ld_relaxed(const unsigned* p) { uint32_t v; asm volatile("ld.relaxed.gpu.global.u32 %0, [%1];" : "=r"(v) : "l"(p) : "memory"); return v; }
__device__ __forceinline__ uint32_t ld_acquire(const unsigned* p) { uint32_t v; asm volatile("ld.acquire.gpu.global.u32 %0, [%1];" : "=r"(v) : "l"(p) : "memory"); return v; }
__device__ __forceinline__ void red_release(unsigned* p) { asm volatile("red.release.gpu.global.add.u32 [%0], 1;" :: "l"(p) : "memory"); }
__device__ __forceinline__ void red_relaxed(unsigned* p) { asm volatile("red.relaxed.gpu.global.add.u32 [%0], 1;" :: "l"(p) : "memory"); }
__device__ __forceinline__ void fence_gpu() { asm volatile("fence.acq_rel.gpu;" ::: "memory"); }
__device__ __forceinline__ void wait_count(const unsigned* p, uint32_t target) {
  int it = 0;
  while (__any_sync(~0u, (int)(ld_acquire(p) - target) < 0)) { if (give_up(++it, 5)) break; __nanosleep(64); }
}

constexpr int G_ST = 32768, G_NST = 7, G_MB = G_ST * G_NST, GB_W = G_MB  , GB_FULL = G_MB + 32, GB_EMPTY = G_MB + 96, GB_EV = G_MB + 160, G_NEV = 48,
              G_SMEM = GB_EV + 16 * G_NEV;

constexpr int C_SW = 0, C_WO = 65536, C_KVQ = 131072, KVQ_ST = 20480, C_QM = 192512, C_MEM = 196608,
              C_VM = 204800  , C_KX = 212992, C_OT = 215040, C_SL = 217088, C_SR = 219136, C_MX = 220160, C_MISC = 221184;
constexpr int MB_WQ = C_MISC, MB_WK = C_MISC + 8, MB_WV = C_MISC + 16, MB_WO = C_MISC + 24, MB_K = C_MISC + 48,
              MB_S = C_MISC + 64, MB_V = C_MISC + 72, MB_KVQ = C_MISC + 80  ;
constexpr int TX_S = 1024, TX_V = 2048;
constexpr int C_WE = C_MISC + 112;
constexpr int C_UP = C_MISC + 128;
constexpr int C_WM = C_MISC + 192;
constexpr int C_XE = C_MISC + 256;
constexpr int C_SU = C_MISC + 704;
constexpr int C_DBG = C_MISC + 768;
constexpr int C_SMEM = C_DBG;

__device__ __forceinline__ const uint8_t* gptr(uint32_t lo, uint32_t hi) { uint64_t r; asm("mov.b64 %0, {%1, %2};" : "=l"(r) : "r"(lo), "r"(hi)); return reinterpret_cast<const uint8_t*>(r); }
__device__ __forceinline__ uint32_t prmt(uint32_t a, uint32_t b, uint32_t s) { uint32_t r; asm("prmt.b32 %0, %1, %2, %3;" : "=r"(r) : "r"(a), "r"(b), "r"(s)); return r; }
#define FENCE_BB asm volatile("{ .reg .pred p; setp.ne.u32 p, %0, 0; @p exit; }" :: "r"(args.zero) : "memory")
__device__ __forceinline__ int fresh(int v) { asm volatile("" : "+r"(v)); return v; }

struct Args {
  CUtensorMap tmq, tmk, tmv, tmo;
  CUtensorMap pw[3];
  CUtensorMap pb[4];
  const bf16* x; const bf16* mem0; const bf16* wo; const bf16* gate_w; bf16* out;
  uint32_t zero;
  uint16_t first[NGC + 2];
  uint32_t job[MAXJOBS];
};
constexpr uint32_t M_CONT = 0, M_STORE = 1, M_RED = 2, M_OUT = 3;
constexpr int K_SMEM = C_SMEM > G_SMEM ? C_SMEM : G_SMEM;

__device__ __forceinline__ void load_a(uint32_t* a, const uint8_t* p0, const uint8_t* p1, int d = 64) {
  ldg128(a, p0); ldg128(a + 4, p1); ldg128(a + 8, p0 + d); ldg128(a + 12, p1 + d);
}
__device__ __forceinline__ void frag_a(uint32_t* u, const uint32_t* a, uint32_t z) {
#pragma unroll
  for (int i = 0; i < 16; i++) { u[i] = a[(i & 8) | ((i & 1) << 2) | (i & 2) | ((i >> 2) & 1)] ^ z; asm volatile("" : "+r"(u[i])); }
}
#define GSTAMP(i)
#define QSTAMP(it, k)
#define PSTAMP(t, i)

__global__ void __launch_bounds__(384, 1)
fused_kernel(const __grid_constant__ Args args) {
  extern __shared__ __align__(1024) uint8_t smem[];
  const int tid = threadIdx.x;
  const int lane = __shfl_sync(~0u, tid & 31, tid & 31);
  const int warp = __shfl_sync(~0u, tid >> 5, 0);
  const int cta = blockIdx.x, h = (cta >> 1) & 31, j = cta & 1;
  const uint32_t sb = smem_u32(smem);

  if (cta >= 64 && tid >= 288 && tid < 288 + 2 * G_NEV) mbar_init(sb + GB_EV + 8 * (tid - 288), 4);
  if (tid == 0 && cta >= 64) {
    for (int i = 0; i < 4; i++) mbar_init(sb + GB_W + 8 * i, 1);
    for (int i = 0; i < G_NST; i++) { mbar_init(sb + GB_FULL + 8 * i, 1); mbar_init(sb + GB_EMPTY + 8 * i, 16); }
    asm volatile("fence.mbarrier_init.release.cluster;" ::: "memory");
    if (cta < 128)
      for (int i = 0; i < 4; i++) {
        mbar_expect_tx(sb + GB_W + 8 * i, 49152);
        for (int b = 0; b < 3; b++) tma5d(sb + b * 65536 + i * 16384, &args.pw[b], h * DH + j * 64, 4 * i, sb + GB_W + 8 * i);
      }
  }
  if (tid == 0 && cta < 64) {
    mbar_init(sb + MB_WQ, 1); mbar_init(sb + MB_WK, 1); mbar_init(sb + MB_WV, 1); mbar_init(sb + MB_WO, 1);
    mbar_init(sb + MB_K, 1); mbar_init(sb + MB_S, 1); mbar_init(sb + MB_V, 9);
    for (int i = 0; i < 3; i++) mbar_init(sb + MB_KVQ + 8 * i, 1);
    asm volatile("fence.mbarrier_init.release.cluster;" ::: "memory");
    const int col = h * DH + j * 64;
    mbar_expect_tx(sb + MB_WQ, 65536); tma2d(sb + C_WO, &args.tmq, col, 0, sb + MB_WQ); tma2d(sb + C_WO + 32768, &args.tmq, col, 256, sb + MB_WQ);
    mbar_expect_tx(sb + MB_WK, 65536); tma2d(sb + C_KVQ, &args.tmk, col, 0, sb + MB_WK); tma2d(sb + C_KVQ + 32768, &args.tmk, col, 256, sb + MB_WK);
    mbar_expect_tx(sb + MB_WV, 65536); tma2d(sb + C_SW, &args.tmv, col, 0, sb + MB_WV); tma2d(sb + C_SW + 32768, &args.tmv, col, 256, sb + MB_WV);
    mbar_expect_tx(sb + MB_K, 1024); mbar_expect_tx(sb + MB_S, TX_S); mbar_expect_tx(sb + MB_V, TX_V);
  }
  PSTAMP(0, 0);
  const uint32_t tag = ldv32(&g_done) / NCTA + 1;
  if (tag != 0) { PSTAMP(0, 1); }
  asm volatile("barrier.cluster.arrive.aligned; barrier.cluster.wait.aligned;" ::: "memory");
  PSTAMP(0, 2);
  uint8_t* const ring = reinterpret_cast<uint8_t*>((reinterpret_cast<uintptr_t>(g_ring) + 8 * RING_SLOT - 1) & ~(uintptr_t)(8 * RING_SLOT - 1));
  auto issue_stage = [&](int seg, int stg) {
    const uint32_t mb = sb + MB_KVQ + 8 * stg;
    mbar_expect_tx(mb, KVQ_ST);
    bulk_g2s(sb + C_KVQ + stg * KVQ_ST, g_qkv + (size_t)(seg * NH + h) * BLK_BYTES + j * 4096, KVQ_ST, mb);
  };

  if (cta >= 64 && warp < 8) {
    asm volatile("setmaxnreg.inc.sync.aligned.u32 232;");
    const int wg = warp >> 2, w = warp & 3, g = lane >> 2, t = lane & 3;
    const uint64_t dsc_hi = (uint64_t)((2048 >> 4) | (1u << 30)) << 32;
    uint32_t A[4][16], U[2][16];
    uint32_t ev = sb + GB_EV + wg * (8 * G_NEV);
    auto publish = [&]() { __syncwarp(); if (lane == 0) mbar_arrive(ev); ev += 8; };
    GSTAMP(0);
    if (cta < 128) {
      float acc[96];
      const uint8_t* p0 = reinterpret_cast<const uint8_t*>(args.x) + (size_t)(wg * 64 + w * 16 + g) * (DM * 2) + t * 16;
#pragma unroll
      for (int i = 0; i < 4; i++) load_a(A[i], p0 + i * 128, p0 + i * 128 + 8192);
      const uint64_t dsc = dsc_hi | (uint64_t)(((sb >> 4) & 0x3FFF) | ((65536 >> 4) << 16));
      uint8_t* dst = g_qkv + (size_t)((2 * wg + (w >> 1)) * NH + h) * BLK_BYTES + 4096 + (w & 1) * 4096 + j * 1024 + lane * 16;
      const int dv = 8192 - (w & 1) * 3584 + j * 3072, dq = (w & 1) * 16384 - 4096 + j * 1024;
      if (wg == 1) bar_sync<1, 256>();
      for (int it = 0; it < 16; it++) {
        QSTAMP(it, 0);
#pragma unroll
        for (int kc = 0; kc < 8; kc++) {
          if (it == 0) mbar_wait(sb + GB_W + 8 * (kc >> 1), 0);
          uint32_t* a = U[kc & 1];
          frag_a(a, A[kc & 3], args.zero);
          wg_fence();
          wgmma_rs192(acc, a[0], a[1], a[2], a[3], dsc + kc * 512, kc != 0);
          wgmma_rs192(acc, a[4], a[5], a[6], a[7], dsc + kc * 512 + 64, 1);
          wgmma_rs192(acc, a[8], a[9], a[10], a[11], dsc + kc * 512 + 256, 1);
          wgmma_rs192(acc, a[12], a[13], a[14], a[15], dsc + kc * 512 + 320, 1);
          wg_commit();
          const uint8_t* pn = p0 + (kc < 4 ? (kc + 4) * 128 : 128 * DM * 2 + (kc - 4) * 128);
          if (kc < 4 || it < 15) load_a(A[kc & 3], pn, pn + 8192);
          if (kc == 0) { QSTAMP(it, 1); }
          if (kc == 4) { QSTAMP(it, 4); }
          if (kc == 3 && it == 0 && wg == 0) bar_arrive<1, 256>();
          wg_wait<1>();
        }
        wg_wait<0>();
        QSTAMP(it, 2);
#pragma unroll
        for (int b = 0; b < 2; b++) {
          const float* d = acc + 16 * b;
          *reinterpret_cast<uint4*>(dst + b * 512) = make_uint4(pack_bf16(d[0], d[1]), pack_bf16(d[4], d[5]), pack_bf16(d[8], d[9]), pack_bf16(d[12], d[13]));
          *reinterpret_cast<uint4*>(dst + b * 512 + 2048) = make_uint4(pack_bf16(d[2], d[3]), pack_bf16(d[6], d[7]), pack_bf16(d[10], d[11]), pack_bf16(d[14], d[15]));
        }
#pragma unroll
        for (int b = 0; b < 4; b++) {
          const float* d = acc + 32 + 8 * b;
          *reinterpret_cast<uint4*>(dst + dv + b * 1024) = make_uint4(movm(pack_bf16(d[0], d[1])), movm(pack_bf16(d[4], d[5])), movm(pack_bf16(d[2], d[3])), movm(pack_bf16(d[6], d[7])));
          *reinterpret_cast<uint4*>(dst + dq + b * 512) = make_uint4(pack_bf16(d[32], d[33]), pack_bf16(d[34], d[35]), pack_bf16(d[36], d[37]), pack_bf16(d[38], d[39]));
        }
        publish();
        QSTAMP(it, 3);
        p0 += 128 * DM * 2; dst += (size_t)4 * NH * BLK_BYTES;
      }
    }
    GSTAMP(1);
    const uint32_t ea = mapa(sb + GB_EMPTY, lane & 1);
    if (lane < 2 * G_NST) mbar_arrive_cluster(ea + 8 * (lane >> 1));
    const int gc = (cta - 64) >> 1;
    const int jn = args.first[gc + 1];
    int ji = args.first[gc];
    const uint64_t dsc = dsc_hi | (uint64_t)(((sb >> 4) & 0x3FFF) | ((8192 >> 4) << 16));
    uint32_t st = 0, ph = 0;
    bool loaded = false, gate_ok = false;
    const uint8_t *p0, *p1;
    int ad;
    auto set_a = [&](uint32_t job) {
      const int m16 = ((job >> 1) & 7) * 16 + j * 8 + warp;
      const bool fin = job & 1;
      p0 = fin ? g_a + (size_t)m16 * A_TILE + ((job >> 8) & 127) * 2048 + t * 128 + g * 16
               : reinterpret_cast<const uint8_t*>(args.x) + (size_t)(m16 * 16 + g) * (DM * 2) + t * 16;
      p1 = p0 + (fin ? 512 : 8 * DM * 2);
      ad = fin ? 1024 : 64;
    };
    auto dep_ptr = [&](uint32_t job) { return (((job >> 8) & 127) < 64 ? g_fo : g_fh) + ((job >> 1) & 7) * 16 + j * 8 + warp; };
    auto dep_cnt = [&](uint32_t job) { return tag * (((job >> 8) & 127) < 64 ? 32u : 14u); };
    if (wg == 1) bar_sync<2, 256>();
    bool lead = wg == 0;
    float acc[128];
    for (; ji < jn; ji++) {
      const uint32_t job = args.job[ji];
      if (!loaded) {
        if (job & 1) wait_count(dep_ptr(job), dep_cnt(job));
        set_a(job);
        load_a(A[0], p0, p1, ad); load_a(A[1], p0 + 2 * ad, p1 + 2 * ad, ad);
      }
      QSTAMP(16 + ji - args.first[gc], 0);
      const uint32_t nxt = args.job[ji + 1];
      const uint32_t dep = ld_relaxed(dep_ptr(nxt));
      const int nk = (job >> 15) & 127;
      uint32_t pst = 0;
      for (int k = 0; k < nk; k += 2) {
#pragma unroll
        for (int u = 0; u < 2; u++) {
          uint32_t* a = U[u];
          mbar_wait(sb + GB_FULL + 8 * st, ph);
          frag_a(a, A[u], args.zero);
          const uint64_t d = dsc + st * (G_ST >> 4);
          wg_fence();
          wgmma_rs256(acc, a[0], a[1], a[2], a[3], d, u != 0 || (k | (job & (1u << 24))) != 0);
          wgmma_rs256(acc, a[4], a[5], a[6], a[7], d + 64, 1);
          wgmma_rs256(acc, a[8], a[9], a[10], a[11], d + 256, 1);
          wgmma_rs256(acc, a[12], a[13], a[14], a[15], d + 320, 1);
          wg_commit();
          if (k + 2 < nk) load_a(A[u], p0 + (2 * u + 4) * ad, p1 + (2 * u + 4) * ad, ad);
          if (u == 0 && k == 2 && lead) { bar_arrive<2, 256>(); lead = false; }
          wg_wait<1>();
          if ((u != 0 || k != 0) && lane < 2) mbar_arrive_cluster(ea + 8 * pst);
          pst = st;
          if (++st == G_NST) { st = 0; ph ^= 1; }
        }
        p0 += 4 * ad; p1 += 4 * ad;
      }
      wg_wait<0>();
      QSTAMP(16 + ji - args.first[gc], 2);
      if (lane < 2) mbar_arrive_cluster(ea + 8 * pst);
      loaded = ji + 1 < jn && (!(nxt & 1) || (int)(dep - dep_cnt(nxt)) >= 0);
      if (loaded) {
        if (nxt & 1) fence_gpu();
        set_a(nxt);
        load_a(A[0], p0, p1, ad); load_a(A[1], p0 + 2 * ad, p1 + 2 * ad, ad);
      }
      QSTAMP(16 + ji - args.first[gc], 1);
      const int m16 = ((job >> 1) & 7) * 16 + j * 8 + warp, n = (job >> 4) & 15;
      const int row = m16 * 16 + g;
      if (!(job & 1)) {
        if (!gate_ok) {
          int it = 0;
          while (!__all_sync(~0u, ldv32(&g_pub[lane]) == tag && ldv32(&g_pub[lane + 32]) == tag)) { if (give_up(++it, 6)) break; }
          fence_gpu();
          gate_ok = true;
        }
        const float s0 = 1.0f - __ldcg(g_gate + row), s1 = 1.0f - __ldcg(g_gate + row + 8);
        uint8_t* q = g_a + (size_t)m16 * A_TILE + (HD / 32 + n * 4) * 1024 + t * 128 + g * 16;
#pragma unroll
        for (int b = 0; b < 4; b++) {
          uint32_t lo[4], hi[4];
#pragma unroll
          for (int i = 0; i < 4; i++) {
            const float* ga = acc + 16 * b + 4 * i;
            float v[4];
#pragma unroll
            for (int e = 0; e < 4; e++) v[e] = __fdividef(ga[64 + e] * (e < 2 ? s0 : s1), 1.0f + ex2(ga[e] * -1.4426950408889634f));
            lo[i] = pack_bf16(v[0], v[1]); hi[i] = pack_bf16(v[2], v[3]);
          }
          *reinterpret_cast<uint4*>(q + 1024 * b) = make_uint4(lo[0], lo[1], lo[2], lo[3]);
          *reinterpret_cast<uint4*>(q + 1024 * b + 512) = make_uint4(hi[0], hi[1], hi[2], hi[3]);
        }
        QSTAMP(16 + ji - args.first[gc], 4);
        publish();
      } else {
        const uint32_t mode = (job >> 22) & 3, parts = job >> 25;
        float4* q = reinterpret_cast<float4*>(g_acc) + (m16 * 2 + n) * 1024;
        if (mode == M_STORE) {
#pragma unroll
          for (int i = 0; i < 32; i++) q[i * 32 + lane] = make_float4(acc[4 * i], acc[4 * i + 1], acc[4 * i + 2], acc[4 * i + 3]);
          publish();
        } else if (mode == M_RED) {
          const unsigned* fc = g_fc + m16 * 2 + n;
          wait_count(fc, (tag - 1) * (parts + 1) + 1);
#pragma unroll
          for (int i = 0; i < 32; i++)
            asm volatile("red.relaxed.gpu.global.add.v4.f32 [%0], {%1,%2,%3,%4};"
                         :: "l"(q + i * 32 + lane), "f"(acc[4 * i]), "f"(acc[4 * i + 1]), "f"(acc[4 * i + 2]), "f"(acc[4 * i + 3]) : "memory");
          publish();
          wait_count(fc, tag * (parts + 1));
          for (int r = ((job >> 8) & 63) >> 2, e = r + (nk >> 2); r < e; r++) {
            const int i = (r >> 3) * 16 + (lane >> 1);
            const float4 u = __ldcg(q + i * 32 + (r & 7) * 4 + (lane & 1) * 2), v = __ldcg(q + i * 32 + (r & 7) * 4 + (lane & 1) * 2 + 1);
            uint2* o = reinterpret_cast<uint2*>(args.out + (size_t)(m16 * 16 + (r & 7)) * DM + n * 256 + (r >> 3) * 128) + lane;
            o[0] = make_uint2(pack_bf16(u.x, u.y), pack_bf16(v.x, v.y));
            o[2 * DM] = make_uint2(pack_bf16(u.z, u.w), pack_bf16(v.z, v.w));
          }
        } else if (mode == M_OUT) {
          uint32_t* o = reinterpret_cast<uint32_t*>(args.out + (size_t)row * DM + n * 256) + t;
#pragma unroll
          for (int i = 0; i < 32; i++) { o[4 * i] = pack_bf16(acc[4 * i], acc[4 * i + 1]); o[4 * i + 4 * DM] = pack_bf16(acc[4 * i + 2], acc[4 * i + 3]); }
        }
      }
      GSTAMP(2 + ji - args.first[gc]);
      QSTAMP(16 + ji - args.first[gc], 3);
    }
    if (lead) bar_arrive<2, 256>();
    asm volatile("barrier.cluster.arrive.aligned; barrier.cluster.wait.aligned;" ::: "memory");
  } else if (cta >= 64) {
    asm volatile("setmaxnreg.dec.sync.aligned.u32 40;");
    if (warp == 8 && lane == 0) {
      const int gc = (cta - 64) >> 1;
      const int jn = args.first[gc + 1];
      uint32_t st = 0, ph = 0;
      for (int ji = args.first[gc]; ji < jn; ji++) {
        const uint32_t job = args.job[ji];
        const int n = (job >> 4) & 15, k0 = (job >> 8) & 127, nk = (job >> 15) & 127;
        const CUtensorMap* tm = &args.pb[(job & 1) ? (k0 < 64 ? 2 : 3) : j];
        const int col = (job & 1) ? n * 256 + j * 128 : n * 128;
        for (int k = 0; k < nk; k++) {
          mbar_wait_cluster(sb + GB_EMPTY + 8 * st, ph);
          const uint32_t mb = sb + GB_FULL + 8 * st, dst = sb + st * G_ST + j * 16384;
          mbar_expect_tx(mb, G_ST);
          tma5d_mc(dst, tm, col, 2 * ((k0 & 63) + k), mb);
          tma5d_mc(dst + 8192, tm, col + 64, 2 * ((k0 & 63) + k), mb);
          if (++st == G_NST) { st = 0; ph ^= 1; }
        }
      }
      atomicAdd(&g_done, 1u);
    } else if (warp > 9) {
      const int wg = warp - 10, gc = (cta - 64) >> 1;
      uint32_t ev = sb + GB_EV + wg * (8 * G_NEV);
      if (cta < 128)
        for (int it = 0; it < 16; it++, ev += 8) {
          mbar_wait(ev, 0);
          fence_gpu();
          if (lane < 4) red_relaxed(g_fq + (4 * it + 2 * wg + (lane >> 1)) * NH + h);
        }
      const int jn = args.first[gc + 1];
      for (int ji = args.first[gc]; ji < jn; ji++) {
        const uint32_t job = args.job[ji], mode = (job >> 22) & 3;
        if ((job & 1) && (mode == M_CONT || mode == M_OUT)) continue;
        const int m16 = ((job >> 1) & 7) * 16 + j * 8 + wg * 4 + (lane & 3);
        mbar_wait(ev, 0);
        ev += 8;
        fence_gpu();
        if (lane < 4) red_relaxed((job & 1) ? g_fc + m16 * 2 + ((job >> 4) & 15) : g_fh + m16);
      }
    }
    __syncwarp();
    asm volatile("barrier.cluster.arrive.aligned; barrier.cluster.wait.aligned;" ::: "memory");
  } else if (warp < 8) {
    asm volatile("setmaxnreg.inc.sync.aligned.u32 " FAT_REGS ";");
    const int gam = warp >> 2, w = warp & 3;
    uint32_t wq[16][4], wk[16][4], wv[16][4];
    const uint32_t l16 = __shfl_sync(~0u, lane * 16, lane);
    float fq, fk, fv;
    uint32_t p0[4], p1[4];
    {
      const uint32_t o = ((lane & 7) + ((lane >> 4) << 3)) * 128 + (((2 * w + ((lane >> 3) & 1)) ^ (lane & 7)) << 4) + gam * 16384 + (w << 12);
      auto load_w = [&](uint32_t (*W)[4], uint32_t base) {
        uint32_t m = 0;
#pragma unroll
        for (int i = 0; i < 16; i++) {
          ldm4t(W[i], base + (o ^ ((i >> 2) << 12)) + ((i >> 1) & 1) * 32768 + (i & 1) * 2048);
          m = absmax2(absmax2(m, absmax2(W[i][0], W[i][1])), absmax2(W[i][2], W[i][3]));
        }
        return __reduce_max_sync(~0u, fold_absmax(m));
      };
      auto to_f16 = [&](uint32_t (*W)[4], uint32_t m) {
        const uint32_t e = max(m >> 7, 15u);
        const float sc = __uint_as_float((268u - e) << 23);
#pragma unroll
        for (int i = 0; i < 64; i++) {
          W[i >> 2][i & 3] = pack_f16(bf_lo(W[i >> 2][i & 3]) * sc, bf_hi(W[i >> 2][i & 3]) * sc);
          asm volatile("" : "+r"(W[i >> 2][i & 3]));
        }
        return __uint_as_float((e - 14u) << 23);
      };
      uint32_t mm = 0;
#pragma unroll
      for (int i = 0; i < 16; i++) {
        const uint4 a = __ldg(reinterpret_cast<const uint4*>(args.mem0) + i * 32 + lane);
        mm = absmax2(mm, absmax2(absmax2(a.x, a.y), absmax2(a.z, a.w)));
      }
      const int E0 = min(max((int)(__reduce_max_sync(~0u, fold_absmax(mm)) >> 7) - 141, -100), 100);
      if (tid == 0) { sts32(sb + C_UP, (uint32_t)(127 + E0) << 23); sts32(sb + C_UP + 4, E0); }
      PSTAMP(0, 3);
      mbar_wait(sb + MB_WQ, 0);
      PSTAMP(0, 4);
      const uint32_t mq = load_w(wq, sb + C_WO);
      mbar_wait(sb + MB_WK, 0);
      const uint32_t mk = load_w(wk, sb + C_KVQ);
      PSTAMP(0, 5);
      bar_sync<10, 384>();
      PSTAMP(0, 6);
      fq = to_f16(wq, mq); fk = to_f16(wk, mk);
      mbar_wait(sb + MB_WV, 0);
      const uint32_t mv = load_w(wv, sb + C_SW);
      if (lane == 0) sts32(sb + C_WM + warp * 4, mv);
      PSTAMP(0, 7);
      bar_sync<11, 384>();
#pragma unroll
      for (int i = 0; i < 8; i++) {
        sts128(sb + C_SW + warp * 8192 + i * 1024 + l16, wq[i][0], wq[i][1], wq[i][2], wq[i][3]);
        sts128(sb + C_SW + warp * 8192 + i * 1024 + 512 + l16, wk[i][0], wk[i][1], wk[i][2], wk[i][3]);
      }
      fv = to_f16(wv, mv);
      PSTAMP(0, 8);
      mbar_wait(sb + MB_WO, 0);
      PSTAMP(0, 9);
      const uint32_t a = C_WO + (warp >> 1) * 16384 + ((lane & 7) + ((lane >> 4) << 3)) * 128 + ((((warp & 1) * 4 + ((lane >> 3) & 1)) ^ (lane & 7)) << 4);
#pragma unroll
      for (int i = 0; i < 8; i++) { ldm4t(wq[i], sb + a + (i << 11)); ldm4t(wk[i], sb + (a ^ 32) + (i << 11)); }
      bar_sync<13, 256>();
#pragma unroll
      for (int i = 0; i < 8; i++) {
        sts128(sb + C_WO + warp * 8192 + i * 1024 + l16, wq[i][0], wq[i][1], wq[i][2], wq[i][3]);
        sts128(sb + C_WO + warp * 8192 + i * 1024 + 512 + l16, wk[i][0], wk[i][1], wk[i][2], wk[i][3]);
      }
#pragma unroll
      for (int i = 0; i < 8; i++) { lds128r(wq[i], sb + C_SW + warp * 8192 + i * 1024 + l16); lds128r(wk[i], sb + C_SW + warp * 8192 + i * 1024 + 512 + l16); }
      const float dn = __uint_as_float((uint32_t)(127 - E0) << 23);
#pragma unroll
      for (int i = 0; i < 4; i++) {
        const uint32_t* mp = reinterpret_cast<const uint32_t*>(args.mem0 + (lane >> 2) * DM + warp * 32 + i * 8 + 2 * (lane & 3));
        const uint32_t u = __ldg(mp), v = __ldg(mp + 128);
        p0[i] = pack_f16(bf_lo(u) * dn, bf_hi(u) * dn);
        p1[i] = pack_f16(bf_lo(v) * dn, bf_hi(v) * dn);
      }
    }
    const uint32_t peer = mapa(sb, j ^ 1);
    const uint32_t sw = sb + warp * 8192 - w * 1024, so = sb - w * 1024;
    const uint32_t rw = (uint32_t)(uintptr_t)ring + (w >> 1) * 8192 + (gam ^ (w >> 1)) * 4096 + (w & 1) * 2048, rh = (uint32_t)((uintptr_t)ring >> 32);
    const int delay = POLL_DELAY;
    const uint32_t mb = sb + C_MEM + gam * 4096;
    PSTAMP(0, 10);
    const uint32_t ma = __shfl_sync(~0u, w * 1024 + lane * 16, lane);
    for (int s = 0;; s++) {
      const uint32_t sz = s & args.zero;
      sts128(mb + ma, p0[0], p0[1], p0[2], p0[3]);
      sts128(mb + 512 + ma, p1[0], p1[1], p1[2], p1[3]);
      asm volatile("{ .reg .pred p; setp.ne.u32 p, %0, 0; @p bar.sync 4, 128; @!p bar.sync 3, 128; }" :: "r"(gam) : "memory");
      float cq[4], ck[4], cw[4], cx[4];
      uint32_t b[8][4], Wo[16][4];
      hma16z(ck, wk[0], p0[0], p0[1]);
      hma16z(cq, wq[0], p0[0], p0[1]);
      hma16z(cx, wk[1], p0[2], p0[3]);
      hma16z(cw, wq[1], p0[2], p0[3]);
      ldv_s(b[2], mb + (ma ^ 1024)); ldv_s(b[3], mb + 512 + (ma ^ 1024));
      FENCE_BB;
      hma16(ck, wk[2], p1[0], p1[1]);
      hma16(cq, wq[2], p1[0], p1[1]);
      hma16(cx, wk[3], p1[2], p1[3]);
      hma16(cw, wq[3], p1[2], p1[3]);
#pragma unroll
      for (int i = 4; i < 6; i++) ldv_s(b[i], mb + (i & 1) * 512 + ((ma | sz) ^ ((i >> 1) * 1024)));
      FENCE_BB;
      hma16(ck, wk[4], b[2][0], b[2][1]);
      hma16(cq, wq[4], b[2][0], b[2][1]);
      hma16(cx, wk[5], b[2][2], b[2][3]);
      hma16(cw, wq[5], b[2][2], b[2][3]);
#pragma unroll
      for (int i = 6; i < 8; i++) ldv_s(b[i], mb + (i & 1) * 512 + ((ma | sz) ^ ((i >> 1) * 1024)));
      FENCE_BB;
      uint32_t mx = absmax2h(absmax2h(absmax2h(p0[0], p0[1]), absmax2h(p0[2], p0[3])), absmax2h(absmax2h(p1[0], p1[1]), absmax2h(p1[2], p1[3])));
      mx = __reduce_max_sync(~0u, absmax2h(mx, mx << 16) & 0x7FFFFFFFu);
#pragma unroll
      for (int i = 3; i < WO_AT; i++) {
        hma16(ck, wk[2 * i], b[i][0], b[i][1]);
        hma16(cq, wq[2 * i], b[i][0], b[i][1]);
        hma16(cx, wk[2 * i + 1], b[i][2], b[i][3]);
        hma16(cw, wq[2 * i + 1], b[i][2], b[i][3]);
      }
      const uint32_t lw = ma | (b[5][0] & b[6][0] & b[7][0] & args.zero);
      FENCE_BB;
      const float up = __uint_as_float(lds32(sb + C_UP));
      sts32(sb + C_MX + warp * 4, mx);
#pragma unroll
      for (int u = 0; u < WO_QK; u++) ldv_s(Wo[u], sw + C_WO + u * 512 + lw);
      FENCE_BB;
#pragma unroll
      for (int i = WO_AT; i < 8; i++) {
        hma16(ck, wk[2 * i], b[i][0], b[i][1]);
        hma16(cq, wq[2 * i], b[i][0], b[i][1]);
        hma16(cx, wk[2 * i + 1], b[i][2], b[i][3]);
        hma16(cw, wq[2 * i + 1], b[i][2], b[i][3]);
      }
      const float uq = up * fq, uk = up * fk;
      stm4(sb + C_QM + gam * 512 + lw, pack_bf16((cq[0] + cw[0]) * uq, (cq[1] + cw[1]) * uq), pack_bf16((cq[2] + cw[2]) * uq, (cq[3] + cw[3]) * uq),
           pack_bf16((ck[0] + cx[0]) * uk, (ck[1] + cx[1]) * uk), pack_bf16((ck[2] + cx[2]) * uk, (ck[3] + cx[3]) * uk));
      bar_arrive<6, 384>();
      FENCE_BB;
      hma16z(cq, wv[0], p0[0], p0[1]);
      hma16z(cw, wv[1], p0[2], p0[3]);
      hma16z(ck, wv[2], p1[0], p1[1]);
      hma16z(cx, wv[3], p1[2], p1[3]);
#pragma unroll
      for (int i = 2; i < 8; i += 2) {
        hma16(cq, wv[2 * i], b[i][0], b[i][1]);
        hma16(cw, wv[2 * i + 1], b[i][2], b[i][3]);
        hma16(ck, wv[2 * i + 2], b[i + 1][0], b[i + 1][1]);
        hma16(cx, wv[2 * i + 3], b[i + 1][2], b[i + 1][3]);
      }
      {
        const float uv = up * fv;
        const uint32_t lo = pack_bf16(((cq[0] + cw[0]) + (ck[0] + cx[0])) * uv, ((cq[1] + cw[1]) + (ck[1] + cx[1])) * uv);
        const uint32_t hi = pack_bf16(((cq[2] + cw[2]) + (ck[2] + cx[2])) * uv, ((cq[3] + cw[3]) + (ck[3] + cx[3])) * uv);
        const uint32_t a = C_VM + (s & 1) * 4096 + j * 2048 + gam * 256 + (lw >> 1);
        st_async64(peer + a, lo, hi, peer + MB_V);
        sts64(sb + a, lo, hi);
        __syncwarp();
        asm volatile("{ .reg .pred p; setp.eq.u32 p, %1, 0; @p mbarrier.arrive.shared::cta.b64 _, [%0]; }" :: "r"(sb + MB_V), "r"(ma & 0x1F0) : "memory");
      }
      if (s == NSEG - 1) break;
#pragma unroll
      for (int u = WO_QK; u < WO_EARLY; u++)
        ldv_s(Wo[u], sw + C_WO + u * 512 + (ma | (u >= WO_QK + WO_PAR ? Wo[u - WO_PAR][0] & args.zero : 0u)));
      const uint32_t lb = ma | sz;
      const uint32_t rp = rw + (s & 7) * RING_SLOT;
      const uint32_t o16 = fresh(rp + j * 16384 + (lb & 0x70) + (lb & 0x80) * 2 + (lb & 0x100) * 4);
      const uint32_t o4 = fresh(rp + 128 + ((lb >> 3) & 0x1C) + (lb & 0x100) * 4 + ((~lb & 16) << 10));
      const uint32_t sa = fresh(lb & 0x30);
      FENCE_BB;
      bar_sync<7, 384>();
      ldm4t(b[0], so + C_OT + ma); ldm4t(b[1], so + C_OT + 512 + ma);
      const float2 su = lds64f(sb + C_SU + sa);
      ldm4t(b[2], so + C_OT + 1024 + ma);
      FENCE_BB;
      mma16z(cx, Wo[3][0], Wo[3][1], Wo[3][2], Wo[3][3], b[0][2], b[0][3]);
      mma16z(ck, Wo[1][0], Wo[1][1], Wo[1][2], Wo[1][3], b[0][0], b[0][1]);
      mma16z(cw, Wo[2][0], Wo[2][1], Wo[2][2], Wo[2][3], b[0][2], b[0][3]);
      mma16z(cq, Wo[0][0], Wo[0][1], Wo[0][2], Wo[0][3], b[0][0], b[0][1]);
      FENCE_BB;
      ldm4t(b[3], so + C_OT + 1536 + ma);
      const float r0 = rcp(su.x), r1 = rcp(su.y);
      const uint32_t sel = ((o16 ^ o4) & 16384) ? 0x3210 : 0x5410;
      Wo[12][0] |= __float_as_uint(r0) & __float_as_uint(r1) & sel & args.zero;
#pragma unroll
      for (int k = 1; k < 4; k++) {
        mma16(cq, Wo[4 * k][0], Wo[4 * k][1], Wo[4 * k][2], Wo[4 * k][3], b[k][0], b[k][1]);
        mma16(ck, Wo[4 * k + 1][0], Wo[4 * k + 1][1], Wo[4 * k + 1][2], Wo[4 * k + 1][3], b[k][0], b[k][1]);
        mma16(cw, Wo[4 * k + 2][0], Wo[4 * k + 2][1], Wo[4 * k + 2][2], Wo[4 * k + 2][3], b[k][2], b[k][3]);
        mma16(cx, Wo[4 * k + 3][0], Wo[4 * k + 3][1], Wo[4 * k + 3][2], Wo[4 * k + 3][3], b[k][2], b[k][3]);
      }
      {
        const uint32_t u3 = movm(pack_f16((ck[2] + cx[2]) * r0, (ck[3] + cx[3]) * r1));
        const uint32_t u0 = movm(pack_f16((cq[0] + cw[0]) * r0, (cq[1] + cw[1]) * r1)), u1 = movm(pack_f16((cq[2] + cw[2]) * r0, (cq[3] + cw[3]) * r1));
        const uint32_t u2 = movm(pack_f16((ck[0] + cx[0]) * r0, (ck[1] + cx[1]) * r1));
        asm volatile("red.relaxed.gpu.global.add.noftz.v4.f16x2 [%0], {%1,%2,%3,%4};"
                     :: "l"(gptr(o16, rh)), "r"(u0), "r"(u1), "r"(u2), "r"(__byte_perm(u3, 0x3C00u, sel)) : "memory");
        asm volatile("{ .reg .pred p; setp.eq.u32 p, %2, 0x5410; @p red.relaxed.gpu.global.add.noftz.f16x2 [%0], %1; }"
                     :: "l"(gptr(o4, rh)), "r"(__byte_perm(u3, 0x3C00u, 0x5432)), "r"(sel) : "memory");
      }
      bar_arrive<9, 384>();
      uint32_t z = 0;
#pragma unroll
      for (int i = 0; i < WV_A; i++) {
        uint32_t* d = (i & 1) ? wk[i >> 1] : wq[i >> 1];
        ldv_s(d, sw + C_SW + i * 512 + (ma | z));
        z = d[0] & args.zero;
      }
#pragma unroll 1
      for (int i = 0; i < delay; i++) z = __shfl_sync(~0u, z, 0);
      const uint8_t* const pa = gptr((o16 & ~16384u) | z, rh);
      uint4 a0 = ldv128(pa), a1 = ldv128(pa + 16384);
      uint32_t b0 = ldv32(gptr(o4, rh));
#pragma unroll
      for (int i = WV_A; i < 16; i++) ldv_s((i & 1) ? wk[i >> 1] : wq[i >> 1], sw + C_SW + i * 512 + ma);
      const bool odd = (o4 & 16384) == 0;
      const uint32_t sel0 = fresh(odd ? 0x5410 : 0x3210), sel1 = fresh(sel0 ^ 0x6600);
      FENCE_BB;
      if (__builtin_expect(__any_sync(~0u, (~((odd ? a0.w : a1.w) & b0) & 0x50000000u) != 0), 0)) {
        int it = 0;
        do {
          a0 = ldv128(pa); a1 = ldv128(pa + 16384); b0 = ldv32(gptr(o4, rh));
        } while (__any_sync(~0u, (~((odd ? a0.w : a1.w) & b0) & 0x50000000u) != 0) && ++it < 65536);
      }
      p0[0] = a0.x; p0[1] = a0.y; p0[2] = a0.z; p0[3] = prmt(a0.w, b0, sel0);
      p1[0] = a1.x; p1[1] = a1.y; p1[2] = a1.z; p1[3] = prmt(a1.w, b0, sel1);
    }
    bar_arrive<7, 384>();
    bar_arrive<9, 384>();
  } else {
    asm volatile("setmaxnreg.dec.sync.aligned.u32 " AUX_REGS ";");
    const int w = warp - 8, at = tid - 256;
    {
      if (at < 80) *reinterpret_cast<uint4*>(ring + (at / 10) * RING_SLOT + (cta >> 1) * 1024 + j * 256 + (at % 10) * 16) = make_uint4(0, 0, 0, 0);
      uint32_t mx = 0, mo = 0;
      const uint4 gw0 = __ldg(reinterpret_cast<const uint4*>(args.gate_w) + lane), gw1 = __ldg(reinterpret_cast<const uint4*>(args.gate_w) + 32 + lane);
#pragma unroll 2
      for (int r = 0; r < 8; r++) {
        const int tok = cta * SEGL + w * 8 + r;
        const uint4* xr = reinterpret_cast<const uint4*>(args.x + (size_t)tok * DM);
        const uint4 a = __ldg(xr + lane), b = __ldg(xr + 32 + lane);
        float acc = bf_lo(a.x) * bf_lo(gw0.x) + bf_hi(a.x) * bf_hi(gw0.x) + bf_lo(a.y) * bf_lo(gw0.y) + bf_hi(a.y) * bf_hi(gw0.y) +
                    bf_lo(a.z) * bf_lo(gw0.z) + bf_hi(a.z) * bf_hi(gw0.z) + bf_lo(a.w) * bf_lo(gw0.w) + bf_hi(a.w) * bf_hi(gw0.w) +
                    bf_lo(b.x) * bf_lo(gw1.x) + bf_hi(b.x) * bf_hi(gw1.x) + bf_lo(b.y) * bf_lo(gw1.y) + bf_hi(b.y) * bf_hi(gw1.y) +
                    bf_lo(b.z) * bf_lo(gw1.z) + bf_hi(b.z) * bf_hi(gw1.z) + bf_lo(b.w) * bf_lo(gw1.w) + bf_hi(b.w) * bf_hi(gw1.w);
        mx = absmax2(absmax2(mx, absmax2(absmax2(a.x, a.y), absmax2(a.z, a.w))), absmax2(absmax2(b.x, b.y), absmax2(b.z, b.w)));
#pragma unroll
        for (int o = 16; o; o >>= 1) acc += __shfl_xor_sync(~0u, acc, o);
        if (lane == 0) g_gate[tok] = __fdividef(1.0f, 1.0f + __expf(-acc));
      }
      const uint4* wr = reinterpret_cast<const uint4*>(args.wo + (size_t)(h * DH + w * 32) * DM + j * 256) + lane;
#pragma unroll 8
      for (int r = 0; r < 32; r++) {
        const uint4 a = __ldg(wr + r * (DM / 8));
        mo = absmax2(mo, absmax2(absmax2(a.x, a.y), absmax2(a.z, a.w)));
      }
      mx = __reduce_max_sync(~0u, fold_absmax(mx));
      mo = __reduce_max_sync(~0u, fold_absmax(mo));
      if (lane == 0) { sts32(sb + C_WM + 32 + w * 4, mx); sts32(sb + C_WM + 48 + w * 4, mo); }
      __threadfence();
    }
    bar_sync<10, 384>();
    if (at == 0) {
      mbar_expect_tx(sb + MB_WO, 65536);
      for (int i = 0; i < 4; i++) tma2d(sb + C_WO + i * 16384, &args.tmo, j * 256 + i * 64, h * DH, sb + MB_WO);
    }
    bar_sync<11, 384>();
    {
      if (at == 0) {
        const uint4 a = lds128(sb + C_WM), b = lds128(sb + C_WM + 16), c = lds128(sb + C_WM + 32), d = lds128(sb + C_WM + 48);
        uint4 r;
        r.x = tag;
        r.y = max(max(c.x, c.y), max(c.z, c.w)) >> 7;
        r.z = max(max(max(a.x, a.y), max(a.z, a.w)), max(max(b.x, b.y), max(b.z, b.w))) >> 7;
        r.w = max(max(d.x, d.y), max(d.z, d.w)) >> 7;
        asm volatile("st.volatile.global.v4.u32 [%0], {%1,%2,%3,%4};" :: "l"(&g_pub[cta]), "r"(r.x), "r"(r.y), "r"(r.z), "r"(r.w) : "memory");
      }
      if (w == 3) {
        uint4 r0, r1;
        int it = 0;
        while (true) {
          r0 = ldv128(&g_pub[lane]); r1 = ldv128(&g_pub[lane + 32]);
          if (__all_sync(~0u, r0.x == tag && r1.x == tag)) break;
          if (give_up(++it, 4)) break;
        }
        PSTAMP(352, 11);
        __threadfence();
        sts32(sb + C_XE + lane * 4, r0.y); sts32(sb + C_XE + 128 + lane * 4, r1.y);
        sts32(sb + C_WE, __reduce_max_sync(~0u, max(r0.z, r1.z)) + __reduce_max_sync(~0u, max(r0.w, r1.w)) - 3 * 126 + 21 - 14);
        for (int i = 0; i < 2; i++) {
          wait_count(g_fq + i * NH + h, tag * 4);
          asm volatile("fence.proxy.async.global;" ::: "memory");
          if (lane == 0) issue_stage(i, i);
        }
      }
    }
    const uint32_t peer = mapa(sb, j ^ 1);
    const float SC = 0.08838834764831845f * 1.4426950408889634f;
    const uint32_t ONE = 0x3F803F80u;
    int st = 0, stp = 0;
    PSTAMP(352, 12);
    int E = (int)lds32(sb + C_UP + 4);
    for (int s = 0; s < NSEG; s++) {
      const uint32_t l16 = fresh(lane) * 16;
      const uint32_t kv = sb + C_KVQ + st * KVQ_ST + (j ? 0 : 4096), qx = sb + C_KVQ + st * KVQ_ST + (j ? 16384 : 0);
      uint32_t fq = 0;
      if (w == 3) fq = ld_relaxed(g_fq + min(s + 2, NSEG - 1) * NH + h + (lane & args.zero));
      mbar_wait1(sb + MB_KVQ + 8 * st, stp);
      if (s == 0) { PSTAMP(352, 13); }
      if (s == 1) { PSTAMP(352, 14); }
      uint32_t va[4][4], vm[2][4], ks0, ks1;
      uint32_t vm_a = C_VM + (s & 1) * 4096 + w * 1024 + (l16 >> 1);
      {
        uint32_t ka[4], kc[4], kb[2][4], q[4][4], kk[4];
        lds128r(ka, kv + w * 2048 + j * 1024 + (w >> 1) * 512 + l16);
        lds128r(kc, kv + w * 2048 + j * 1024 + 512 - (w >> 1) * 512 + l16);
#pragma unroll
        for (int i = 0; i < 4; i++) lds128r(va[i], kv + 8192 + w * 2048 + i * 512 + l16);
#pragma unroll
        for (int i = 0; i < 4; i++) {
          kb[0][i] = (w & 1) ? ka[i ^ 2] : ka[i]; kb[1][i] = (w & 1) ? kc[i ^ 2] : kc[i];
          asm volatile("" : "+r"(kb[0][i]), "+r"(kb[1][i]));
        }
        uint32_t q_a = w * 512 + l16, r_a = peer + C_SR + (q_a >> 1);
        uint32_t q_0 = w * 1024 + (l16 & 0x70) + (l16 & 0x80) * 4 + ((l16 >> 1) & 0x80), q_1 = q_0 ^ 1024, q_2 = q_0 ^ 2048, q_3 = q_0 ^ 3072;
        asm volatile("" : "+r"(q_0), "+r"(q_1), "+r"(q_2), "+r"(q_3), "+r"(r_a), "+r"(vm_a));
        FENCE_BB;
        bar_sync<6, 384>();
        float s0[4], s1[4], s2[4];
        ldm4t(q[0], sb + C_QM + q_0); ldm4t(q[1], sb + C_QM + q_1); ldm4t(kk, sb + C_QM + 256 + q_0); ldm4t(q[2], sb + C_QM + q_2); ldm4t(q[3], sb + C_QM + q_3);
        FENCE_BB;
        mma16z(s0, q[0][0], q[0][1], q[0][2], q[0][3], kb[0][0], kb[0][1]);
        mma16z(s1, q[1][0], q[1][1], q[1][2], q[1][3], kb[0][2], kb[0][3]);
        ks0 = hadd2(kk[0], kk[1]); ks1 = hadd2(kk[2], kk[3]);
        mma16z(s2, q[0][0], q[0][1], q[0][2], q[0][3], ks0, ks1);
        mma16(s0, q[2][0], q[2][1], q[2][2], q[2][3], kb[1][0], kb[1][1]);
        mma16(s1, q[3][0], q[3][1], q[3][2], q[3][3], kb[1][2], kb[1][3]);
        const float x2 = s2[0] + s2[2], x3 = s2[1] + s2[3];
        const float x0 = (s0[0] + s0[2]) + (s1[0] + s1[2]), x1 = (s0[1] + s0[3]) + (s1[1] + s1[3]);
        st_async64(r_a, pack_bf16(x0, x1), pack_bf16(x2, x3), peer + MB_S);
        FENCE_BB;
        sts128(sb + C_SL + q_a, __float_as_uint(x0), __float_as_uint(x1), __float_as_uint(x2), __float_as_uint(x3));
        const uint4 ma = lds128(sb + C_MX), mc = lds128(sb + C_MX + 16);
        const int xe = lds32(sb + C_XE + s * 4), we = lds32(sb + C_WE);
        bar_sync<8, 128>();
        float4 u[4];
#pragma unroll
        for (int i = 0; i < 4; i++) u[i] = lds128f(sb + C_SL + i * 512 + l16);
        const bool s_ok = mbar_try(sb + MB_S, s & 1);
        FENCE_BB;
        E = max((int)(max(max(max(ma.x, ma.y), max(ma.z, ma.w)), max(max(mc.x, mc.y), max(mc.z, mc.w))) >> 26) + 112 + E, xe) + we;
        E = min(max(E, -100), 100);
        float up = __uint_as_float((uint32_t)(127 + E) << 23);
        sts32(sb + C_UP, __float_as_uint(up));
        float z0 = (u[0].z + u[1].z) + (u[2].z + u[3].z), z1 = (u[0].w + u[1].w) + (u[2].w + u[3].w);
        asm volatile("" : "+f"(z0), "+f"(z1), "+f"(up));
        if (__builtin_expect(!s_ok, 0)) mbar_wait1(sb + MB_S, s & 1);
        uint2 r[4];
#pragma unroll
        for (int i = 0; i < 4; i++) r[i] = lds64(sb + C_SR + i * 256 + (l16 >> 1));
        const bool v_ok = mbar_try(sb + MB_V, s & 1);
        FENCE_BB;
        const uint32_t rm = hadd2(hadd2(r[0].y, r[1].y), hadd2(r[2].y, r[3].y));
        const float sv[10] = {u[0].x + bf_lo(r[0].x), u[0].y + bf_hi(r[0].x), u[1].x + bf_lo(r[1].x), u[1].y + bf_hi(r[1].x),
                              u[2].x + bf_lo(r[2].x), u[2].y + bf_hi(r[2].x), u[3].x + bf_lo(r[3].x), u[3].y + bf_hi(r[3].x),
                              z0 + bf_lo(rm), z1 + bf_hi(rm)};
        float m = fmaxf(fmaxf(fmaxf(sv[0], sv[1]), fmaxf(sv[2], sv[3])), fmaxf(fmaxf(sv[4], sv[5]), fmaxf(sv[6], sv[7])));
        m = fmaxf(m, fmaxf(sv[8], sv[9])) * SC;
        const float m1 = __shfl_xor_sync(~0u, m, 1), m2 = __shfl_xor_sync(~0u, m, 2), m3 = __shfl_xor_sync(~0u, m, 3);
        float e[10], o0[4], o1[4], o2[4], o3[4], su[4];
#pragma unroll
        for (int i = 0; i < 4; i++) e[i] = ex2v(fmaf(sv[i], SC, -m));
        FENCE_BB;
        const float c = ex2v(m - fmaxf(fmaxf(m, m1), fmaxf(m2, m3)));
#pragma unroll
        for (int i = 4; i < 10; i++) e[i] = ex2v(fmaf(sv[i], SC, -m));
        if (__builtin_expect(!v_ok, 0)) mbar_wait1(sb + MB_V, s & 1);
        lds64r(vm[0], sb + vm_a); lds64r(vm[0] + 2, sb + vm_a + 256); lds64r(vm[1], sb + vm_a + 512); lds64r(vm[1] + 2, sb + vm_a + 768);
        {
          const uint32_t pa = pack_bf16(e[0] * c, e[1] * c), pb = pack_bf16(e[2] * c, e[3] * c);
          const uint32_t pc = pack_bf16(e[4] * c, e[5] * c), pd = pack_bf16(e[6] * c, e[7] * c), pe = pack_bf16(e[8] * c, e[9] * c);
          mma16z(o0, va[0][0], va[0][1], va[0][2], va[0][3], pa, pb);
          mma16z(o1, va[2][0], va[2][1], va[2][2], va[2][3], pa, pb);
          mma16z(su, ONE, ONE, ONE, ONE, pa, pb);
          mma16z(o2, va[1][0], va[1][1], va[1][2], va[1][3], pc, pd);
          mma16z(o3, va[3][0], va[3][1], va[3][2], va[3][3], pc, pd);
          mma16(o0, vm[0][0], vm[0][1], vm[0][2], vm[0][3], pe, pe);
          mma16(o1, vm[1][0], vm[1][1], vm[1][2], vm[1][3], pe, pe);
          mma16(su, ONE, ONE, ONE, ONE, pc, pd);
          mma8(su, ONE, ONE, pe);
#pragma unroll
          for (int i = 0; i < 4; i++) { o0[i] += o2[i]; o1[i] += o3[i]; }
        }
        stm4(sb + C_OT + q_a, pack_bf16(o0[0], o0[1]), pack_bf16(o0[2], o0[3]), pack_bf16(o1[0], o1[1]), pack_bf16(o1[2], o1[3]));
        asm volatile("{ .reg .pred p; setp.lt.u32 p, %3, 64; @p st.shared.v2.f32 [%0], {%1,%2}; }"
                     :: "r"(sb + C_SU + q_a), "f"(su[0] * up), "f"(su[1] * up), "r"(q_a) : "memory");
        bar_arrive<7, 384>();
        FENCE_BB;
        st_async64(r_a + (C_KX - C_SR) + j * 1024, ks0, ks1, peer + MB_K);
        sts64(sb + C_KX + j * 1024 + (q_a >> 1), ks0, ks1);
      }
      if (w == 0) {
        float g0, g1;
        asm volatile("ld.global.cg.f32 %0, [%2]; ld.global.cg.f32 %1, [%2+32];" : "=f"(g0), "=f"(g1) : "l"(g_gate + s * SEGL + 16 * j + (l16 >> 6)) : "memory");
        bar_sync<9, 384>();
        float sc[5][4];
#pragma unroll
        for (int i = 0; i < 4; i++) {
          uint32_t a[4], c[4], kb[4][4], km[4];
          lds128r(a, qx + i * 1024 + l16);
          lds128r(kb[0], kv + i * 512 + l16); lds128r(kb[1], kv + 2048 + i * 512 + l16);
          lds128r(c, qx + i * 1024 + 512 + l16);
          lds128r(kb[2], kv + 4096 + i * 512 + l16); lds128r(kb[3], kv + 6144 + i * 512 + l16);
          if (i == 0) mbar_wait1(sb + MB_K, s & 1);
          lds64r(km, sb + C_KX + i * 512 + (l16 >> 1)); lds64r(km + 2, sb + C_KX + i * 512 + 256 + (l16 >> 1));
#pragma unroll
          for (int n = 0; n < 4; n++) {
            if (i == 0) mma16z(sc[n], a[0], a[1], a[2], a[3], kb[n][0], kb[n][1]);
            else mma16(sc[n], a[0], a[1], a[2], a[3], kb[n][0], kb[n][1]);
          }
          if (i == 0) mma16z(sc[4], a[0], a[1], a[2], a[3], km[0], km[1]);
          else mma16(sc[4], a[0], a[1], a[2], a[3], km[0], km[1]);
#pragma unroll
          for (int n = 0; n < 4; n++) mma16(sc[n], c[0], c[1], c[2], c[3], kb[n][2], kb[n][3]);
          mma16(sc[4], c[0], c[1], c[2], c[3], km[2], km[3]);
        }
        if (l16 == 0 && s < NSEG - 1) mbar_expect_tx(sb + MB_K, 1024);
        const float NEG = -1.0e9f * 1.4426950408889634f;
        const int d = 16 * j + (int)(l16 >> 6) - (int)((l16 >> 3) & 6);
#pragma unroll
        for (int n = 0; n < 4; n++) {
          sc[n][0] = d >= 8 * n ? sc[n][0] * SC : NEG; sc[n][1] = d >= 8 * n + 1 ? sc[n][1] * SC : NEG;
          sc[n][2] = d >= 8 * n - 8 ? sc[n][2] * SC : NEG; sc[n][3] = d >= 8 * n - 7 ? sc[n][3] * SC : NEG;
        }
#pragma unroll
        for (int e = 0; e < 4; e++) sc[4][e] *= SC;
        float x0 = fmaxf(sc[0][0], sc[0][1]), x1 = fmaxf(sc[0][2], sc[0][3]);
#pragma unroll
        for (int n = 1; n < 5; n++) { x0 = fmaxf(x0, fmaxf(sc[n][0], sc[n][1])); x1 = fmaxf(x1, fmaxf(sc[n][2], sc[n][3])); }
        x0 = fmaxf(x0, __shfl_xor_sync(~0u, x0, 1)); x1 = fmaxf(x1, __shfl_xor_sync(~0u, x1, 1));
        x0 = fmaxf(x0, __shfl_xor_sync(~0u, x0, 2)); x1 = fmaxf(x1, __shfl_xor_sync(~0u, x1, 2));
        float y0 = 0.f, y1 = 0.f;
#pragma unroll
        for (int n = 0; n < 5; n++) {
          sc[n][0] = ex2(sc[n][0] - x0); sc[n][1] = ex2(sc[n][1] - x0); sc[n][2] = ex2(sc[n][2] - x1); sc[n][3] = ex2(sc[n][3] - x1);
          y0 += sc[n][0] + sc[n][1]; y1 += sc[n][2] + sc[n][3];
        }
        y0 += __shfl_xor_sync(~0u, y0, 1); y1 += __shfl_xor_sync(~0u, y1, 1);
        y0 += __shfl_xor_sync(~0u, y0, 2); y1 += __shfl_xor_sync(~0u, y1, 2);
        const float r0 = rcp(y0) * g0, r1 = rcp(y1) * g1;
        sts128(kv + l16, pack_bf16(sc[0][0] * r0, sc[0][1] * r0), pack_bf16(sc[1][0] * r0, sc[1][1] * r0),
               pack_bf16(sc[2][0] * r0, sc[2][1] * r0), pack_bf16(sc[3][0] * r0, sc[3][1] * r0));
        sts128(kv + 512 + l16, pack_bf16(sc[0][2] * r1, sc[0][3] * r1), pack_bf16(sc[1][2] * r1, sc[1][3] * r1),
               pack_bf16(sc[2][2] * r1, sc[2][3] * r1), pack_bf16(sc[3][2] * r1, sc[3][3] * r1));
        sts64(kv + 1024 + (l16 >> 1), pack_bf16(sc[4][0] * r0, sc[4][1] * r0), pack_bf16(sc[4][2] * r1, sc[4][3] * r1));
#pragma unroll
        for (int i = 0; i < 4; i++) lds128r(va[i], kv + 8192 + i * 512 + l16);
        lds64r(vm[0], sb + vm_a); lds64r(vm[0] + 2, sb + vm_a + 256); lds64r(vm[1], sb + vm_a + 512); lds64r(vm[1] + 2, sb + vm_a + 768);
      } else {
        bar_arrive<9, 384>();
        if (w == 3) {
          if (lane == 0) {
            asm volatile("cp.async.bulk.wait_group 0;" ::: "memory");
            if (s > 0) FLAG_O(g_fo + 2 * (s - 1) + j);
            if (s + 2 < NSEG) {
              int it = 0;
              while ((int)(fq - tag * 4) < 0) { if (give_up(++it, 5)) break; fq = ld_acquire(g_fq + (s + 2) * NH + h); }
              asm volatile("fence.proxy.async.global;" ::: "memory");
              issue_stage(s + 2, st ? st - 1 : 2);
            }
          }
        } else if (w == 2) {
          if (lane == 0 && s < NSEG - 1) { mbar_expect_tx(sb + MB_S, TX_S); mbar_expect_tx(sb + MB_V, TX_V); }
        } else if (s >= 2) {
          if (lane < 10) asm volatile("st.global.v4.u32 [%0], {%1,%1,%1,%1};" :: "l"(ring + ((s - 2) & 7) * RING_SLOT + (cta >> 1) * 1024 + j * 256 + lane * 16), "r"(0) : "memory");
        }
        __syncwarp();
      }
      bar_sync<8, 128>();
      {
        uint32_t p[2][4], p4[2];
        lds128r(p[0], kv + l16); lds128r(p[1], kv + 512 + l16); lds64r(p4, kv + 1024 + (l16 >> 1));
        float o[4][4];
#pragma unroll
        for (int i = 0; i < 4; i++) mma16z(o[i], va[(i & 1) * 2][0], va[(i & 1) * 2][1], va[(i & 1) * 2][2], va[(i & 1) * 2][3], p[i >> 1][0], p[i >> 1][1]);
#pragma unroll
        for (int i = 0; i < 4; i++) mma16(o[i], va[(i & 1) * 2 + 1][0], va[(i & 1) * 2 + 1][1], va[(i & 1) * 2 + 1][2], va[(i & 1) * 2 + 1][3], p[i >> 1][2], p[i >> 1][3]);
#pragma unroll
        for (int i = 0; i < 4; i++) mma16(o[i], vm[i & 1][0], vm[i & 1][1], vm[i & 1][2], vm[i & 1][3], p4[i >> 1], p4[i >> 1]);
#pragma unroll
        for (int i = 0; i < 2; i++)
          stm4t(qx + w * 1024 + i * 512 + l16, pack_bf16(o[2 * i][0], o[2 * i][1]), pack_bf16(o[2 * i][2], o[2 * i][3]),
                pack_bf16(o[2 * i + 1][0], o[2 * i + 1][1]), pack_bf16(o[2 * i + 1][2], o[2 * i + 1][3]));
        asm volatile("fence.proxy.async.shared::cta;" ::: "memory");
      }
      if (w == 3) {
        bar_sync<5, 128>();
        if (lane == 0) {
          asm volatile("cp.async.bulk.global.shared::cta.bulk_group [%0], [%1], 4096;" :: "l"(g_a + (size_t)(2 * s + j) * A_TILE + h * 4096), "r"(qx) : "memory");
          asm volatile("cp.async.bulk.commit_group;" ::: "memory");
        }
        __syncwarp();
      } else {
        bar_arrive<5, 128>();
      }
      if (++st == 3) { st = 0; stp ^= 1; }
    }
    if (w == 3 && lane == 0) {
      asm volatile("cp.async.bulk.wait_group 0;" ::: "memory");
      FLAG_O(g_fo + 2 * (NSEG - 1) + j);
    }
    if (w == 0 && lane == 0) atomicAdd(&g_done, 1u);
  }
}

typedef CUresult (*EncodeFn)(CUtensorMap*, CUtensorMapDataType, cuuint32_t, void*, const cuuint64_t*, const cuuint64_t*, const cuuint32_t*,
                             const cuuint32_t*, CUtensorMapInterleave, CUtensorMapSwizzle, CUtensorMapL2promotion, CUtensorMapFloatOOBfill);
static void make_map(EncodeFn enc, CUtensorMap* tm, const void* base, uint64_t cols, uint64_t rows, uint32_t bc, uint32_t br) {
  cuuint64_t dims[2] = {cols, rows};
  cuuint64_t strides[1] = {cols * 2};
  cuuint32_t box[2] = {bc, br}, es[2] = {1, 1};
  enc(tm, CU_TENSOR_MAP_DATA_TYPE_BFLOAT16, 2, const_cast<void*>(base), dims, strides, box, es, CU_TENSOR_MAP_INTERLEAVE_NONE,
      CU_TENSOR_MAP_SWIZZLE_128B, CU_TENSOR_MAP_L2_PROMOTION_L2_256B, CU_TENSOR_MAP_FLOAT_OOB_FILL_NONE);
}

static int make_map5(EncodeFn enc, CUtensorMap* tm, const void* base, uint64_t cols, uint64_t rows, uint32_t groups, bool regroup) {
  const uint64_t rb = cols * 2;
  cuuint64_t dims[5] = {cols, 2, 4, 4, rows / 32};
  cuuint64_t strides[4] = {rb, (regroup ? 8 : 2) * rb, (regroup ? 2 : 8) * rb, 32 * rb};
  cuuint32_t box[5] = {64, 2, 4, 4, groups}, es[5] = {1, 1, 1, 1, 1};
  return (int)enc(tm, CU_TENSOR_MAP_DATA_TYPE_BFLOAT16, 5, const_cast<void*>(base), dims, strides, box, es, CU_TENSOR_MAP_INTERLEAVE_NONE,
                  CU_TENSOR_MAP_SWIZZLE_128B, CU_TENSOR_MAP_L2_PROMOTION_L2_256B, CU_TENSOR_MAP_FLOAT_OOB_FILL_NONE);
}

static void build_schedule(Args& a) {
  static uint32_t lists[NGC][48];
  int cnt[NGC] = {}, nglu[NGC];
  auto fin = [](int p, int n, int k0, int nk, uint32_t mode, int keep, int parts) {
    return (uint32_t)(1 | p << 1 | n << 4 | k0 << 8 | nk << 15) | mode << 22 | (uint32_t)keep << 24 | (uint32_t)parts << 25;
  };
  const int early = GLU_EARLY, order[8] = {4, 5, 6, 7, 0, 1, 2, 3};
  int left = 112 - 2 * early;
  for (int c = 0; c < NGC; c++) { nglu[c] = c < 6 ? 0 : 3; left -= nglu[c]; }
  for (int c = 31; left > 0; c--, left--) nglu[c]++;
  int g = 0;
  auto glu = [&](int c) { lists[c][cnt[c]++] = (uint32_t)(order[g / 14] << 1 | (g % 14) << 4 | 8 << 15); g++; };
  for (int i = 0; i < early; i++) { glu(32); glu(33); }
  for (int r = 0; r < 8; r++) for (int c = NGC - 1; c >= 0; c--) if (r < nglu[c] && g < 112) glu(c);
  for (int c = 0; c < 8; c++) { lists[c][cnt[c]++] = fin(c >> 1, c & 1, 0, 64, M_CONT, 0, 0); lists[c][cnt[c]++] = fin(c >> 1, c & 1, 64, 28, M_OUT, 1, 0); }
  for (int c = 8; c < 10; c++) { lists[c][cnt[c]++] = fin(4, c & 1, 64, 28, M_CONT, 0, 0); lists[c][cnt[c]++] = fin(4, c & 1, 0, 64, M_OUT, 1, 0); }
  for (int c = 10; c < 16; c++) lists[c][cnt[c]++] = fin(c >> 1, c & 1, 64, 28, M_STORE, 0, 0);
  for (int c = 16; c < 20; c++) lists[c][cnt[c]++] = fin(5, c & 1, ((c - 16) >> 1) * 32, 32, M_RED, 0, 2);
  for (int c = 20; c < 28; c++) lists[c][cnt[c]++] = fin(6, c & 1, ((c - 20) >> 1) * 16, 16, M_RED, 0, 4);
  for (int c = 0, q = 0; c < NGC; c++) if (c != 8 && c != 9) { lists[c][cnt[c]++] = fin(7, q & 1, (q >> 1) * 4, 4, M_RED, 0, 16); q++; }
  int o = 0;
  for (int c = 0; c < NGC; c++) { a.first[c] = (uint16_t)o; for (int i = 0; i < cnt[c]; i++) a.job[o++] = lists[c][i]; }
  a.first[NGC] = (uint16_t)o; a.first[NGC + 1] = 0; a.zero = 0;
  for (; o < MAXJOBS; o++) a.job[o] = 0;
}

extern "C" void kernel_launch(void* const* d_in, const int* in_sizes, int n_in, void* d_out, int out_size) {
  (void)in_sizes; (void)n_in; (void)out_size;
  const bf16 *wq = (const bf16*)d_in[2], *wk = (const bf16*)d_in[3], *wv = (const bf16*)d_in[4], *wo = (const bf16*)d_in[5],
             *wg = (const bf16*)d_in[8], *wu = (const bf16*)d_in[9], *wd = (const bf16*)d_in[10];
  static EncodeFn enc = nullptr;
  static Args a;
  if (!enc) {
    void* fn = nullptr; cudaDriverEntryPointQueryResult qr;
    cudaGetDriverEntryPoint("cuTensorMapEncodeTiled", &fn, cudaEnableDefault, &qr);
    enc = (EncodeFn)fn;
    cudaFuncSetAttribute(fused_kernel, cudaFuncAttributeMaxDynamicSharedMemorySize, K_SMEM);
    build_schedule(a);
  }
  make_map(enc, &a.tmq, wq, HD, DM, 64, 256); make_map(enc, &a.tmk, wk, HD, DM, 64, 256); make_map(enc, &a.tmv, wv, HD, DM, 64, 256);
  make_map(enc, &a.tmo, wo, DM, HD, 64, 128);
  int rc = make_map5(enc, &a.pw[0], wk, HD, DM, 4, true) | make_map5(enc, &a.pw[1], wv, HD, DM, 4, true) | make_map5(enc, &a.pw[2], wq, HD, DM, 4, true) |
           make_map5(enc, &a.pb[0], wg, FF, DM, 2, true) | make_map5(enc, &a.pb[1], wu, FF, DM, 2, true) |
           make_map5(enc, &a.pb[2], wo, DM, HD, 2, true) | make_map5(enc, &a.pb[3], wd, DM, FF, 2, false);
  if (rc) return;
  a.x = (const bf16*)d_in[0]; a.mem0 = (const bf16*)d_in[1]; a.wo = wo; a.gate_w = (const bf16*)d_in[11]; a.out = (bf16*)d_out;
  cudaLaunchConfig_t cfg = {};
  cfg.gridDim = dim3(NCTA); cfg.blockDim = dim3(384); cfg.dynamicSmemBytes = K_SMEM; cfg.stream = cudaStreamPerThread;
  cudaLaunchAttribute at[1];
  at[0].id = cudaLaunchAttributeClusterDimension; at[0].val.clusterDim.x = 2; at[0].val.clusterDim.y = 1; at[0].val.clusterDim.z = 1;
  cfg.attrs = at; cfg.numAttrs = 1;
  cudaLaunchKernelEx(&cfg, fused_kernel, a);
}
```

```cpp
#include <cuda_runtime.h>
#include <cuda_bf16.h>
#include <cuda_fp16.h>
#include <cuda.h>
#include <stdint.h>

typedef __nv_bfloat16 bf16;
#define FAT_REGS "216"
#define AUX_REGS "72"
#define WO_QK 6
#define WO_AT 5
#define WO_EARLY 16
#define WO_PAR 2
#define WV_A 10
#define FLAG_O red_relaxed
#define GLU_EARLY 12
#define LAG_K 2
#define LAG_U 1
#define POLL_DELAY 5

constexpr int SEQ = 2048, DM = 512, NH = 32, DH = 128, SEGL = 32, NSEG = 64, FF = 1792;
constexpr int HD = NH * DH;
constexpr int KA = HD + FF;
constexpr int NCTA = 132, NGC = 34, MAXJOBS = 320;
constexpr int BLK_BYTES = 24576;
constexpr int RING_SLOT = 32768;
constexpr int A_TILE = KA / 32 * 1024;
constexpr int SPIN_LIMIT = 1 << 20;

__device__ __align__(1024) uint8_t g_qkv[(size_t)NSEG * NH * BLK_BYTES];
__device__ __align__(1024) uint8_t g_a[(size_t)SEQ * KA * 2];
__device__ __align__(1024) float g_acc[(size_t)SEQ * DM];
__device__ unsigned g_fq[NSEG * NH];
__device__ unsigned g_fh[128];
__device__ unsigned g_fo[128];
__device__ unsigned g_fc[256];
__device__ __align__(1024) uint8_t g_ring[16 * RING_SLOT];
__device__ __align__(128) unsigned g_gate[SEQ];
__device__ uint4 g_pub[64];
__device__ unsigned g_done;
__device__ int g_err;

__device__ __forceinline__ uint32_t smem_u32(const void* p) { return (uint32_t)__cvta_generic_to_shared(p); }
__device__ __forceinline__ uint32_t mapa(uint32_t a, uint32_t rank) { uint32_t r; asm volatile("mapa.shared::cluster.u32 %0, %1, %2;" : "=r"(r) : "r"(a), "r"(rank)); return r; }
__device__ __forceinline__ void mbar_init(uint32_t a, uint32_t cnt) { asm volatile("mbarrier.init.shared::cta.b64 [%0], %1;" :: "r"(a), "r"(cnt) : "memory"); }
__device__ __forceinline__ void mbar_expect_tx(uint32_t a, uint32_t bytes) { asm volatile("mbarrier.arrive.expect_tx.shared::cta.b64 _, [%0], %1;" :: "r"(a), "r"(bytes) : "memory"); }
__device__ __forceinline__ bool mbar_try(uint32_t a, uint32_t parity) {
  uint32_t ok;
  asm volatile("{ .reg .pred p; mbarrier.try_wait.parity.shared::cta.b64 p, [%1], %2; selp.u32 %0, 1, 0, p; }" : "=r"(ok) : "r"(a), "r"(parity) : "memory");
  return ok;
}
__device__ __forceinline__ bool mbar_try_cluster(uint32_t a, uint32_t parity) {
  uint32_t ok;
  asm volatile("{ .reg .pred p; mbarrier.try_wait.parity.acquire.cluster.shared::cta.b64 p, [%1], %2; selp.u32 %0, 1, 0, p; }" : "=r"(ok) : "r"(a), "r"(parity) : "memory");
  return ok;
}
__device__ __forceinline__ bool give_up(int it, int code) {
  if ((it & 1023) != 0) return false;
  if (it < SPIN_LIMIT && *reinterpret_cast<volatile int*>(&g_err) == 0) return false;
  if (it >= SPIN_LIMIT) g_err = code;
  return true;
}
__device__ __forceinline__ void mbar_wait(uint32_t a, uint32_t parity) {
  int it = 0;
  while (!mbar_try(a, parity)) { if (give_up(++it, 1)) break; }
}
__device__ __forceinline__ void mbar_wait1(uint32_t a, uint32_t parity) {
  asm volatile("{ .reg .pred p; .reg .u32 c; mov.u32 c, 0;\nW: mbarrier.try_wait.parity.shared::cta.b64 p, [%0], %1;\n"
               "add.u32 c, c, 1; setp.lt.and.u32 p, c, 65536, !p; @p bra W; }" :: "r"(a), "r"(parity) : "memory");
}
__device__ __forceinline__ void mbar_wait_cluster(uint32_t a, uint32_t parity) {
  int it = 0;
  while (!mbar_try_cluster(a, parity)) { if (give_up(++it, 2)) break; }
}
template <int ID, int N> __device__ __forceinline__ void bar_sync() { asm volatile("bar.sync %0, %1;" :: "n"(ID), "n"(N) : "memory"); }
template <int ID, int N> __device__ __forceinline__ void bar_arrive() { asm volatile("bar.arrive %0, %1;" :: "n"(ID), "n"(N) : "memory"); }
__device__ __forceinline__ void bar_sync_id(int id, int n) { asm volatile("bar.sync %0, %1;" :: "r"(id), "r"(n) : "memory"); }
__device__ __forceinline__ void tma2d(uint32_t dst, const CUtensorMap* tm, int c0, int c1, uint32_t mb) {
  asm volatile("cp.async.bulk.tensor.2d.shared::cluster.global.mbarrier::complete_tx::bytes [%0], [%1, {%3, %4}], [%2];"
               :: "r"(dst), "l"((uint64_t)tm), "r"(mb), "r"(c0), "r"(c1) : "memory");
}
__device__ __forceinline__ void bulk_g2s(uint32_t dst, const void* src, uint32_t bytes, uint32_t mb) {
  asm volatile("cp.async.bulk.shared::cluster.global.mbarrier::complete_tx::bytes [%0], [%1], %2, [%3];"
               :: "r"(dst), "l"(src), "r"(bytes), "r"(mb) : "memory");
}
__device__ __forceinline__ void ldm4(uint32_t* r, uint32_t a) {
  asm volatile("ldmatrix.sync.aligned.m8n8.x4.shared.b16 {%0,%1,%2,%3}, [%4];" : "=r"(r[0]), "=r"(r[1]), "=r"(r[2]), "=r"(r[3]) : "r"(a) : "memory");
}
__device__ __forceinline__ void ldm4t(uint32_t* r, uint32_t a) {
  asm volatile("ldmatrix.sync.aligned.m8n8.x4.trans.shared.b16 {%0,%1,%2,%3}, [%4];" : "=r"(r[0]), "=r"(r[1]), "=r"(r[2]), "=r"(r[3]) : "r"(a) : "memory");
}
__device__ __forceinline__ void stm4(uint32_t a, uint32_t r0, uint32_t r1, uint32_t r2, uint32_t r3) {
  asm volatile("stmatrix.sync.aligned.m8n8.x4.shared.b16 [%0], {%1,%2,%3,%4};" :: "r"(a), "r"(r0), "r"(r1), "r"(r2), "r"(r3) : "memory");
}
__device__ __forceinline__ void stm4t(uint32_t a, uint32_t r0, uint32_t r1, uint32_t r2, uint32_t r3) {
  asm volatile("stmatrix.sync.aligned.m8n8.x4.trans.shared.b16 [%0], {%1,%2,%3,%4};" :: "r"(a), "r"(r0), "r"(r1), "r"(r2), "r"(r3) : "memory");
}
__device__ __forceinline__ void hma16(float* d, const uint32_t* a, uint32_t b0, uint32_t b1) {
  asm volatile("mma.sync.aligned.m16n8k16.row.col.f32.f16.f16.f32 {%0,%1,%2,%3}, {%4,%5,%6,%7}, {%8,%9}, {%0,%1,%2,%3};"
               : "+f"(d[0]), "+f"(d[1]), "+f"(d[2]), "+f"(d[3]) : "r"(a[0]), "r"(a[1]), "r"(a[2]), "r"(a[3]), "r"(b0), "r"(b1));
}
__device__ __forceinline__ void hma16z(float* d, const uint32_t* a, uint32_t b0, uint32_t b1) {
  asm volatile("mma.sync.aligned.m16n8k16.row.col.f32.f16.f16.f32 {%0,%1,%2,%3}, {%4,%5,%6,%7}, {%8,%9}, {%10,%10,%10,%10};"
               : "=f"(d[0]), "=f"(d[1]), "=f"(d[2]), "=f"(d[3]) : "r"(a[0]), "r"(a[1]), "r"(a[2]), "r"(a[3]), "r"(b0), "r"(b1), "f"(0.f));
}
__device__ __forceinline__ void mma16(float* d, uint32_t a0, uint32_t a1, uint32_t a2, uint32_t a3, uint32_t b0, uint32_t b1) {
  asm volatile("mma.sync.aligned.m16n8k16.row.col.f32.bf16.bf16.f32 {%0,%1,%2,%3}, {%4,%5,%6,%7}, {%8,%9}, {%0,%1,%2,%3};"
               : "+f"(d[0]), "+f"(d[1]), "+f"(d[2]), "+f"(d[3]) : "r"(a0), "r"(a1), "r"(a2), "r"(a3), "r"(b0), "r"(b1));
}
__device__ __forceinline__ void mma16z(float* d, uint32_t a0, uint32_t a1, uint32_t a2, uint32_t a3, uint32_t b0, uint32_t b1) {
  asm volatile("mma.sync.aligned.m16n8k16.row.col.f32.bf16.bf16.f32 {%0,%1,%2,%3}, {%4,%5,%6,%7}, {%8,%9}, {%10,%10,%10,%10};"
               : "=f"(d[0]), "=f"(d[1]), "=f"(d[2]), "=f"(d[3]) : "r"(a0), "r"(a1), "r"(a2), "r"(a3), "r"(b0), "r"(b1), "f"(0.f));
}
__device__ __forceinline__ void mma8(float* d, uint32_t a0, uint32_t a1, uint32_t b0) {
  asm volatile("mma.sync.aligned.m16n8k8.row.col.f32.bf16.bf16.f32 {%0,%1,%2,%3}, {%4,%5}, {%6}, {%0,%1,%2,%3};"
               : "+f"(d[0]), "+f"(d[1]), "+f"(d[2]), "+f"(d[3]) : "r"(a0), "r"(a1), "r"(b0));
}
__device__ __forceinline__ void mma8z(float* d, uint32_t a0, uint32_t a1, uint32_t b0) {
  asm volatile("mma.sync.aligned.m16n8k8.row.col.f32.bf16.bf16.f32 {%0,%1,%2,%3}, {%4,%5}, {%6}, {%7,%7,%7,%7};"
               : "=f"(d[0]), "=f"(d[1]), "=f"(d[2]), "=f"(d[3]) : "r"(a0), "r"(a1), "r"(b0), "f"(0.f));
}
__device__ __forceinline__ uint32_t pack_bf16(float lo, float hi) { uint32_t r; asm("cvt.rn.bf16x2.f32 %0, %1, %2;" : "=r"(r) : "f"(hi), "f"(lo)); return r; }
__device__ __forceinline__ uint32_t pack_f16(float lo, float hi) { uint32_t r; asm("cvt.rn.f16x2.f32 %0, %1, %2;" : "=r"(r) : "f"(hi), "f"(lo)); return r; }
__device__ __forceinline__ float2 unpack_f16(uint32_t v) { return __half22float2(*reinterpret_cast<__half2*>(&v)); }
__device__ __forceinline__ uint32_t absmax2(uint32_t a, uint32_t b) { uint32_t r; asm("max.xorsign.abs.bf16x2 %0, %1, %2;" : "=r"(r) : "r"(a), "r"(b)); return r; }
__device__ __forceinline__ uint32_t absmax2h(uint32_t a, uint32_t b) { uint32_t r; asm("max.xorsign.abs.f16x2 %0, %1, %2;" : "=r"(r) : "r"(a), "r"(b)); return r; }
__device__ __forceinline__ uint32_t hadd2(uint32_t a, uint32_t b) { uint32_t r; asm("add.rn.bf16x2 %0, %1, %2;" : "=r"(r) : "r"(a), "r"(b)); return r; }
__device__ __forceinline__ void sts64(uint32_t a, uint32_t x, uint32_t y) { asm volatile("st.shared.v2.u32 [%0], {%1,%2};" :: "r"(a), "r"(x), "r"(y) : "memory"); }
__device__ __forceinline__ uint2 lds64(uint32_t a) { uint2 v; asm volatile("ld.shared.v2.u32 {%0,%1}, [%2];" : "=r"(v.x), "=r"(v.y) : "r"(a) : "memory"); return v; }
__device__ __forceinline__ void lds64r(uint32_t* r, uint32_t a) { asm volatile("ld.shared.v2.u32 {%0,%1}, [%2];" : "=r"(r[0]), "=r"(r[1]) : "r"(a) : "memory"); }
__device__ __forceinline__ void ldv_s(uint32_t* r, uint32_t a) {
  asm volatile("ld.volatile.shared.v4.u32 {%0,%1,%2,%3}, [%4];" : "=r"(r[0]), "=r"(r[1]), "=r"(r[2]), "=r"(r[3]) : "r"(a) : "memory");
}
__device__ __forceinline__ float ex2v(float x) { float r; asm volatile("ex2.approx.ftz.f32 %0, %1;" : "=f"(r) : "f"(x)); return r; }
__device__ __forceinline__ uint32_t fold_absmax(uint32_t m) { m &= 0x7FFF7FFFu; return max(m & 0xFFFFu, m >> 16); }
__device__ __forceinline__ float ex2(float x) { float r; asm("ex2.approx.ftz.f32 %0, %1;" : "=f"(r) : "f"(x)); return r; }
__device__ __forceinline__ void sts32(uint32_t a, uint32_t v) { asm volatile("st.shared.u32 [%0], %1;" :: "r"(a), "r"(v) : "memory"); }
__device__ __forceinline__ void sts64f(uint32_t a, float x, float y) { asm volatile("st.shared.v2.f32 [%0], {%1,%2};" :: "r"(a), "f"(x), "f"(y) : "memory"); }
__device__ __forceinline__ float2 lds64f(uint32_t a) { float2 v; asm volatile("ld.shared.v2.f32 {%0,%1}, [%2];" : "=f"(v.x), "=f"(v.y) : "r"(a) : "memory"); return v; }
__device__ __forceinline__ uint32_t lds32(uint32_t a) { uint32_t v; asm volatile("ld.shared.u32 %0, [%1];" : "=r"(v) : "r"(a) : "memory"); return v; }
__device__ __forceinline__ uint4 lds128(uint32_t a) { uint4 v; asm volatile("ld.shared.v4.u32 {%0,%1,%2,%3}, [%4];" : "=r"(v.x), "=r"(v.y), "=r"(v.z), "=r"(v.w) : "r"(a) : "memory"); return v; }
__device__ __forceinline__ void st_async32(uint32_t a, uint32_t v, uint32_t mb) {
  asm volatile("st.async.weak.shared::cluster.mbarrier::complete_tx::bytes.b32 [%0], %1, [%2];" :: "r"(a), "r"(v), "r"(mb) : "memory");
}
__device__ __forceinline__ void st_async64(uint32_t a, uint32_t x, uint32_t y, uint32_t mb) {
  asm volatile("st.async.weak.shared::cluster.mbarrier::complete_tx::bytes.v2.b32 [%0], {%1,%2}, [%3];" :: "r"(a), "r"(x), "r"(y), "r"(mb) : "memory");
}
__device__ __forceinline__ void st_async128(uint32_t a, uint32_t x, uint32_t y, uint32_t z, uint32_t w, uint32_t mb) {
  asm volatile("st.async.weak.shared::cluster.mbarrier::complete_tx::bytes.v4.b32 [%0], {%1,%2,%3,%4}, [%5];" :: "r"(a), "r"(x), "r"(y), "r"(z), "r"(w), "r"(mb) : "memory");
}
__device__ __forceinline__ void sts128(uint32_t a, uint32_t x, uint32_t y, uint32_t z, uint32_t w) {
  asm volatile("st.shared.v4.u32 [%0], {%1,%2,%3,%4};" :: "r"(a), "r"(x), "r"(y), "r"(z), "r"(w) : "memory");
}
__device__ __forceinline__ void lds128r(uint32_t* r, uint32_t a) {
  asm volatile("ld.shared.v4.u32 {%0,%1,%2,%3}, [%4];" : "=r"(r[0]), "=r"(r[1]), "=r"(r[2]), "=r"(r[3]) : "r"(a) : "memory");
}
__device__ __forceinline__ float4 lds128f(uint32_t a) { float4 v; asm volatile("ld.shared.v4.f32 {%0,%1,%2,%3}, [%4];" : "=f"(v.x), "=f"(v.y), "=f"(v.z), "=f"(v.w) : "r"(a) : "memory"); return v; }
__device__ __forceinline__ void mbar_arrive(uint32_t a) { asm volatile("mbarrier.arrive.shared::cta.b64 _, [%0];" :: "r"(a) : "memory"); }
__device__ __forceinline__ uint32_t movm(uint32_t a) { uint32_t d; asm volatile("movmatrix.sync.aligned.m8n8.trans.b16 %0, %1;" : "=r"(d) : "r"(a)); return d; }
__device__ __forceinline__ float rcp(float x) { float r; asm("rcp.approx.ftz.f32 %0, %1;" : "=f"(r) : "f"(x)); return r; }
__device__ __forceinline__ uint32_t f16_to_bf16(uint32_t v) { const float2 f = unpack_f16(v); return pack_bf16(f.x, f.y); }
__device__ __forceinline__ uint4 ldv128(const void* p) {
  uint4 v; asm volatile("ld.volatile.global.v4.u32 {%0,%1,%2,%3}, [%4];" : "=r"(v.x), "=r"(v.y), "=r"(v.z), "=r"(v.w) : "l"(p) : "memory"); return v;
}
__device__ __forceinline__ uint32_t ldv32(const void* p) { uint32_t v; asm volatile("ld.volatile.global.u32 %0, [%1];" : "=r"(v) : "l"(p) : "memory"); return v; }
__device__ __forceinline__ float bf_lo(uint32_t v) { return __uint_as_float(v << 16); }
__device__ __forceinline__ float bf_hi(uint32_t v) { return __uint_as_float(v & 0xFFFF0000u); }

__device__ __forceinline__ void wgmma_rs192(float* d, uint32_t a0, uint32_t a1, uint32_t a2, uint32_t a3, uint64_t desc, int acc) {
  asm volatile("{ .reg .pred p; setp.ne.b32 p, %101, 0;\n"
    "wgmma.mma_async.sync.aligned.m64n192k16.f32.bf16.bf16 {%0,%1,%2,%3,%4,%5,%6,%7,%8,%9,%10,%11,%12,%13,%14,%15,%16,%17,%18,%19,%20,%21,%22,%23,%24,%25,%26,%27,%28,%29,%30,%31,%32,%33,%34,%35,%36,%37,%38,%39,%40,%41,%42,%43,%44,%45,%46,%47,%48,%49,%50,%51,%52,%53,%54,%55,%56,%57,%58,%59,%60,%61,%62,%63,%64,%65,%66,%67,%68,%69,%70,%71,%72,%73,%74,%75,%76,%77,%78,%79,%80,%81,%82,%83,%84,%85,%86,%87,%88,%89,%90,%91,%92,%93,%94,%95}, {%96,%97,%98,%99}, %100, p, 1, 1, 1; }"
    :
      "+f"(d[0]), "+f"(d[1]), "+f"(d[2]), "+f"(d[3]), "+f"(d[4]), "+f"(d[5]), "+f"(d[6]), "+f"(d[7]), "+f"(d[8]), "+f"(d[9]), "+f"(d[10]), "+f"(d[11]),
      "+f"(d[12]), "+f"(d[13]), "+f"(d[14]), "+f"(d[15]), "+f"(d[16]), "+f"(d[17]), "+f"(d[18]), "+f"(d[19]), "+f"(d[20]), "+f"(d[21]), "+f"(d[22]), "+f"(d[23]),
      "+f"(d[24]), "+f"(d[25]), "+f"(d[26]), "+f"(d[27]), "+f"(d[28]), "+f"(d[29]), "+f"(d[30]), "+f"(d[31]), "+f"(d[32]), "+f"(d[33]), "+f"(d[34]), "+f"(d[35]),
      "+f"(d[36]), "+f"(d[37]), "+f"(d[38]), "+f"(d[39]), "+f"(d[40]), "+f"(d[41]), "+f"(d[42]), "+f"(d[43]), "+f"(d[44]), "+f"(d[45]), "+f"(d[46]), "+f"(d[47]),
      "+f"(d[48]), "+f"(d[49]), "+f"(d[50]), "+f"(d[51]), "+f"(d[52]), "+f"(d[53]), "+f"(d[54]), "+f"(d[55]), "+f"(d[56]), "+f"(d[57]), "+f"(d[58]), "+f"(d[59]),
      "+f"(d[60]), "+f"(d[61]), "+f"(d[62]), "+f"(d[63]), "+f"(d[64]), "+f"(d[65]), "+f"(d[66]), "+f"(d[67]), "+f"(d[68]), "+f"(d[69]), "+f"(d[70]), "+f"(d[71]),
      "+f"(d[72]), "+f"(d[73]), "+f"(d[74]), "+f"(d[75]), "+f"(d[76]), "+f"(d[77]), "+f"(d[78]), "+f"(d[79]), "+f"(d[80]), "+f"(d[81]), "+f"(d[82]), "+f"(d[83]),
      "+f"(d[84]), "+f"(d[85]), "+f"(d[86]), "+f"(d[87]), "+f"(d[88]), "+f"(d[89]), "+f"(d[90]), "+f"(d[91]), "+f"(d[92]), "+f"(d[93]), "+f"(d[94]), "+f"(d[95])
    : "r"(a0), "r"(a1), "r"(a2), "r"(a3), "l"(desc), "r"(acc));
}

__device__ __forceinline__ void wgmma_rs256(float* d, uint32_t a0, uint32_t a1, uint32_t a2, uint32_t a3, uint64_t desc, int acc) {
  asm volatile("{ .reg .pred p; setp.ne.b32 p, %133, 0;\n"
    "wgmma.mma_async.sync.aligned.m64n256k16.f32.bf16.bf16 {%0,%1,%2,%3,%4,%5,%6,%7,%8,%9,%10,%11,%12,%13,%14,%15,%16,%17,%18,%19,%20,%21,%22,%23,%24,%25,%26,%27,%28,%29,%30,%31,%32,%33,%34,%35,%36,%37,%38,%39,%40,%41,%42,%43,%44,%45,%46,%47,%48,%49,%50,%51,%52,%53,%54,%55,%56,%57,%58,%59,%60,%61,%62,%63,%64,%65,%66,%67,%68,%69,%70,%71,%72,%73,%74,%75,%76,%77,%78,%79,%80,%81,%82,%83,%84,%85,%86,%87,%88,%89,%90,%91,%92,%93,%94,%95,%96,%97,%98,%99,%100,%101,%102,%103,%104,%105,%106,%107,%108,%109,%110,%111,%112,%113,%114,%115,%116,%117,%118,%119,%120,%121,%122,%123,%124,%125,%126,%127}, {%128,%129,%130,%131}, %132, p, 1, 1, 1; }"
    :
      "+f"(d[0]), "+f"(d[1]), "+f"(d[2]), "+f"(d[3]), "+f"(d[4]), "+f"(d[5]), "+f"(d[6]), "+f"(d[7]), "+f"(d[8]), "+f"(d[9]), "+f"(d[10]), "+f"(d[11]),
      "+f"(d[12]), "+f"(d[13]), "+f"(d[14]), "+f"(d[15]), "+f"(d[16]), "+f"(d[17]), "+f"(d[18]), "+f"(d[19]), "+f"(d[20]), "+f"(d[21]), "+f"(d[22]), "+f"(d[23]),
      "+f"(d[24]), "+f"(d[25]), "+f"(d[26]), "+f"(d[27]), "+f"(d[28]), "+f"(d[29]), "+f"(d[30]), "+f"(d[31]), "+f"(d[32]), "+f"(d[33]), "+f"(d[34]), "+f"(d[35]),
      "+f"(d[36]), "+f"(d[37]), "+f"(d[38]), "+f"(d[39]), "+f"(d[40]), "+f"(d[41]), "+f"(d[42]), "+f"(d[43]), "+f"(d[44]), "+f"(d[45]), "+f"(d[46]), "+f"(d[47]),
      "+f"(d[48]), "+f"(d[49]), "+f"(d[50]), "+f"(d[51]), "+f"(d[52]), "+f"(d[53]), "+f"(d[54]), "+f"(d[55]), "+f"(d[56]), "+f"(d[57]), "+f"(d[58]), "+f"(d[59]),
      "+f"(d[60]), "+f"(d[61]), "+f"(d[62]), "+f"(d[63]), "+f"(d[64]), "+f"(d[65]), "+f"(d[66]), "+f"(d[67]), "+f"(d[68]), "+f"(d[69]), "+f"(d[70]), "+f"(d[71]),
      "+f"(d[72]), "+f"(d[73]), "+f"(d[74]), "+f"(d[75]), "+f"(d[76]), "+f"(d[77]), "+f"(d[78]), "+f"(d[79]), "+f"(d[80]), "+f"(d[81]), "+f"(d[82]), "+f"(d[83]),
      "+f"(d[84]), "+f"(d[85]), "+f"(d[86]), "+f"(d[87]), "+f"(d[88]), "+f"(d[89]), "+f"(d[90]), "+f"(d[91]), "+f"(d[92]), "+f"(d[93]), "+f"(d[94]), "+f"(d[95]),
      "+f"(d[96]), "+f"(d[97]), "+f"(d[98]), "+f"(d[99]), "+f"(d[100]), "+f"(d[101]), "+f"(d[102]), "+f"(d[103]), "+f"(d[104]), "+f"(d[105]), "+f"(d[106]), "+f"(d[107]),
      "+f"(d[108]), "+f"(d[109]), "+f"(d[110]), "+f"(d[111]), "+f"(d[112]), "+f"(d[113]), "+f"(d[114]), "+f"(d[115]), "+f"(d[116]), "+f"(d[117]), "+f"(d[118]), "+f"(d[119]),
      "+f"(d[120]), "+f"(d[121]), "+f"(d[122]), "+f"(d[123]), "+f"(d[124]), "+f"(d[125]), "+f"(d[126]), "+f"(d[127])
    : "r"(a0), "r"(a1), "r"(a2), "r"(a3), "l"(desc), "r"(acc));
}

__device__ __forceinline__ void wg_fence() { asm volatile("wgmma.fence.sync.aligned;" ::: "memory"); }
__device__ __forceinline__ void wg_commit() { asm volatile("wgmma.commit_group.sync.aligned;" ::: "memory"); }
template <int N> __device__ __forceinline__ void wg_wait() { asm volatile("wgmma.wait_group.sync.aligned %0;" :: "n"(N) : "memory"); }
__device__ __forceinline__ void tma5d(uint32_t dst, const CUtensorMap* tm, int c0, int c4, uint32_t mb) {
  asm volatile("cp.async.bulk.tensor.5d.shared::cluster.global.mbarrier::complete_tx::bytes [%0], [%1, {%3, %5, %5, %5, %4}], [%2];"
               :: "r"(dst), "l"((uint64_t)tm), "r"(mb), "r"(c0), "r"(c4), "r"(0) : "memory");
}
__device__ __forceinline__ void tma5d_mc(uint32_t dst, const CUtensorMap* tm, int c0, int c4, uint32_t mb) {
  asm volatile("cp.async.bulk.tensor.5d.shared::cluster.global.mbarrier::complete_tx::bytes.multicast::cluster [%0], [%1, {%3, %5, %5, %5, %4}], [%2], %6;"
               :: "r"(dst), "l"((uint64_t)tm), "r"(mb), "r"(c0), "r"(c4), "r"(0), "h"((unsigned short)3) : "memory");
}
__device__ __forceinline__ void mbar_arrive_cluster(uint32_t a) { asm volatile("mbarrier.arrive.shared::cluster.b64 _, [%0];" :: "r"(a) : "memory"); }
__device__ __forceinline__ void ldg128(uint32_t* r, const uint8_t* p) {
  asm volatile("ld.global.L1::no_allocate.v4.u32 {%0,%1,%2,%3}, [%4];" : "=r"(r[0]), "=r"(r[1]), "=r"(r[2]), "=r"(r[3]) : "l"(p) : "memory");
}
__device__ __forceinline__ uint32_t ld_relaxed(const unsigned* p) { uint32_t v; asm volatile("ld.relaxed.gpu.global.u32 %0, [%1];" : "=r"(v) : "l"(p) : "memory"); return v; }
__device__ __forceinline__ void st_relaxed(unsigned* p, uint32_t v) { asm volatile("st.relaxed.gpu.global.u32 [%0], %1;" :: "l"(p), "r"(v) : "memory"); }
__device__ __forceinline__ uint32_t ld_acquire(const unsigned* p) { uint32_t v; asm volatile("ld.acquire.gpu.global.u32 %0, [%1];" : "=r"(v) : "l"(p) : "memory"); return v; }
__device__ __forceinline__ void red_release(unsigned* p) { asm volatile("red.release.gpu.global.add.u32 [%0], 1;" :: "l"(p) : "memory"); }
__device__ __forceinline__ void red_relaxed(unsigned* p) { asm volatile("red.relaxed.gpu.global.add.u32 [%0], 1;" :: "l"(p) : "memory"); }
__device__ __forceinline__ void fence_gpu() { asm volatile("fence.acq_rel.gpu;" ::: "memory"); }
__device__ __forceinline__ void wait_count(const unsigned* p, uint32_t target) {
  int it = 0;
  while (__any_sync(~0u, (int)(ld_acquire(p) - target) < 0)) { if (give_up(++it, 5)) break; __nanosleep(64); }
}

__device__ __forceinline__ void check_gate(uint32_t& g0, uint32_t& g1, const unsigned* p, uint32_t tag) {
  int it = 0;
  while (__builtin_expect(__any_sync(~0u, (((g0 ^ tag) | (g1 ^ tag)) & 15) != 0), 0)) {
    if (give_up(++it, 6)) break;
    g0 = ld_relaxed(p); g1 = ld_relaxed(p + 8);
  }
}

constexpr int G_ST = 32768, G_NST = 7, G_MB = G_ST * G_NST, GB_W = G_MB  , GB_FULL = G_MB + 32, GB_EMPTY = G_MB + 96, GB_EV = G_MB + 160, G_NEV = 48,
              G_SMEM = GB_EV + 16 * G_NEV;

constexpr int C_SW = 0, C_WO = 65536, C_KVQ = 131072, KVQ_ST = 20480, C_QM = 192512, C_MEM = 196608,
              C_VM = 204800  , C_KX = 212992, C_OT = 215040, C_SL = 217088, C_SR = 219136, C_MX = 220160, C_MISC = 221184;
constexpr int MB_WQ = C_MISC, MB_WK = C_MISC + 8, MB_WV = C_MISC + 16, MB_WO = C_MISC + 24, MB_K = C_MISC + 48,
              MB_S = C_MISC + 64, MB_V = C_MISC + 72, MB_KVQ = C_MISC + 80  ;
constexpr int TX_S = 1024, TX_V = 2048;
constexpr int C_WE = C_MISC + 112;
constexpr int C_UP = C_MISC + 128;
constexpr int C_WM = C_MISC + 512;
constexpr int C_XE = C_MISC + 256;
constexpr int C_SU = C_MISC + 704;
constexpr int C_DBG = C_MISC + 768;
constexpr int C_SMEM = C_DBG;

__device__ __forceinline__ const uint8_t* gptr(uint32_t lo, uint32_t hi) { uint64_t r; asm("mov.b64 %0, {%1, %2};" : "=l"(r) : "r"(lo), "r"(hi)); return reinterpret_cast<const uint8_t*>(r); }
__device__ __forceinline__ uint32_t prmt(uint32_t a, uint32_t b, uint32_t s) { uint32_t r; asm("prmt.b32 %0, %1, %2, %3;" : "=r"(r) : "r"(a), "r"(b), "r"(s)); return r; }
#define FENCE_BB asm volatile("{ .reg .pred p; setp.ne.u32 p, %0, 0; @p exit; }" :: "r"(args.zero) : "memory")
__device__ __forceinline__ int fresh(int v) { asm volatile("" : "+r"(v)); return v; }

struct Args {
  CUtensorMap tmq, tmk, tmv, tmo;
  CUtensorMap pw[3];
  CUtensorMap pb[4];
  const bf16* x; const bf16* mem0; const bf16* wo; const bf16* gate_w; bf16* out;
  uint32_t zero;
  uint16_t first[NGC + 2];
  uint32_t job[MAXJOBS];
};
constexpr uint32_t M_CONT = 0, M_STORE = 1, M_RED = 2, M_OUT = 3;
constexpr int K_TAG = C_SMEM > G_SMEM ? C_SMEM : G_SMEM, K_SMEM = K_TAG + 32;

__device__ __forceinline__ void load_a(uint32_t* a, const uint8_t* p0, const uint8_t* p1, int d = 64) {
  ldg128(a, p0); ldg128(a + 4, p1); ldg128(a + 8, p0 + d); ldg128(a + 12, p1 + d);
}
__device__ __forceinline__ void frag_a(uint32_t* u, const uint32_t* a, uint32_t z) {
#pragma unroll
  for (int i = 0; i < 16; i++) { u[i] = a[(i & 8) | ((i & 1) << 2) | (i & 2) | ((i >> 2) & 1)] ^ z; asm volatile("" : "+r"(u[i])); }
}
#define GSTAMP(i)
#define QSTAMP(it, k)
#define PSTAMP(t, i)

__global__ void __launch_bounds__(384, 1)
fused_kernel(const __grid_constant__ Args args) {
  extern __shared__ __align__(1024) uint8_t smem[];
  const int tid = threadIdx.x;
  const int lane = __shfl_sync(~0u, tid & 31, tid & 31);
  const int warp = __shfl_sync(~0u, tid >> 5, 0);
  const int cta = blockIdx.x, h = (cta >> 1) & 31, j = cta & 1;
  const uint32_t sb = smem_u32(smem);
  if (warp == (cta < 64 ? 2 : 11) && lane < 11 && (lane < 4) == (cta < 64)) asm volatile("prefetch.tensormap [%0];" :: "l"(&args.tmq + lane) : "memory");
  if (tid == (cta < 64 ? 32 : 320)) sts32(sb + K_TAG, ldv32(&g_done) / NCTA + 1);

  if (cta >= 64 && tid >= 288 && tid < 288 + 2 * G_NEV) mbar_init(sb + GB_EV + 8 * (tid - 288), 4);
  if (tid == 256 && cta >= 64) {
    for (int i = 0; i < 4; i++) mbar_init(sb + GB_W + 8 * i, 1);
    for (int i = 0; i < G_NST; i++) { mbar_init(sb + GB_FULL + 8 * i, 1); mbar_init(sb + GB_EMPTY + 8 * i, 16); }
    asm volatile("fence.mbarrier_init.release.cluster;" ::: "memory");
  }
  if (tid == 0 && cta < 64) {
    mbar_init(sb + MB_WQ, 1); mbar_init(sb + MB_WK, 1); mbar_init(sb + MB_WV, 1); mbar_init(sb + MB_WO, 1);
    mbar_init(sb + MB_K, 1); mbar_init(sb + MB_S, 1); mbar_init(sb + MB_V, 9);
    for (int i = 0; i < 3; i++) mbar_init(sb + MB_KVQ + 8 * i, 1);
    asm volatile("fence.mbarrier_init.release.cluster;" ::: "memory");
    mbar_expect_tx(sb + MB_K, 1024); mbar_expect_tx(sb + MB_S, TX_S); mbar_expect_tx(sb + MB_V, TX_V);
  }
  PSTAMP(0, 0);
  auto start = [&]() {
    asm volatile("barrier.cluster.arrive.relaxed.aligned; bar.sync 0; barrier.cluster.wait.aligned;" ::: "memory");
    return lds32(sb + K_TAG);
  };
  uint8_t* const ring = reinterpret_cast<uint8_t*>((reinterpret_cast<uintptr_t>(g_ring) + 8 * RING_SLOT - 1) & ~(uintptr_t)(8 * RING_SLOT - 1));
  auto issue_stage = [&](int seg, int stg) {
    const uint32_t mb = sb + MB_KVQ + 8 * stg;
    mbar_expect_tx(mb, KVQ_ST);
    bulk_g2s(sb + C_KVQ + stg * KVQ_ST, g_qkv + (size_t)(seg * NH + h) * BLK_BYTES + j * 4096, KVQ_ST, mb);
  };

  if (cta >= 64 && warp < 8) {
    const int wg = warp >> 2, w = warp & 3, g = lane >> 2, t = lane & 3;
    const uint64_t dsc_hi = (uint64_t)((2048 >> 4) | (1u << 30)) << 32;
    uint32_t A[4][16], U[2][16];
    {
      const uint8_t* p0 = reinterpret_cast<const uint8_t*>(args.x) + (size_t)(wg * 64 + w * 16 + g) * (DM * 2) + t * 16;
      if (wg == 0 && cta < 128) {
#pragma unroll
        for (int i = 0; i < 4; i++) load_a(A[i], p0 + i * 128, p0 + i * 128 + 8192);
#pragma unroll
        for (int i = 0; i < 16; i++)
          asm volatile("cp.async.cg.shared.global [%0], [%1], 16;" :: "r"(sb + 196608 + i * 2048 + tid * 16), "l"(p0 + 512 + (i >> 1) * 64 + (i & 1) * 8192) : "memory");
        asm volatile("cp.async.wait_all;" ::: "memory");
      }
    }
    const uint32_t tag = start();
    if (wg == 1) {
      const uint8_t* p0 = reinterpret_cast<const uint8_t*>(args.x) + (size_t)(wg * 64 + w * 16 + g) * (DM * 2) + t * 16;
#pragma unroll
      for (int i = 0; i < 4; i++) load_a(A[i], p0 + i * 128, p0 + i * 128 + 8192);
    }
    asm volatile("setmaxnreg.inc.sync.aligned.u32 232;");
    uint32_t ev = sb + GB_EV + wg * (8 * G_NEV);
    auto publish = [&]() { __syncwarp(); if (lane == 0) mbar_arrive(ev); ev += 8; };
    GSTAMP(0);
    if (cta < 128) {
      float acc[96];
      const uint8_t* p0 = reinterpret_cast<const uint8_t*>(args.x) + (size_t)(wg * 64 + w * 16 + g) * (DM * 2) + t * 16;
      const uint64_t dsc = dsc_hi | (uint64_t)(((sb >> 4) & 0x3FFF) | ((65536 >> 4) << 16));
      uint8_t* dst = g_qkv + (size_t)((2 * wg + (w >> 1)) * NH + h) * BLK_BYTES + 4096 + (w & 1) * 4096 + j * 1024 + lane * 16;
      const int dv = 8192 - (w & 1) * 3584 + j * 3072, dq = (w & 1) * 16384 - 4096 + j * 1024;
      if (wg == 1) bar_sync<1, 256>();
      for (int it = 0; it < 16; it++) {
        QSTAMP(it, 0);
#pragma unroll
        for (int kc = 0; kc < 8; kc++) {
          if (it == 0) mbar_wait(sb + GB_W + 8 * (kc >> 1), 0);
          uint32_t* a = U[kc & 1];
          frag_a(a, A[kc & 3], args.zero);
          wg_fence();
          wgmma_rs192(acc, a[0], a[1], a[2], a[3], dsc + kc * 512, kc != 0);
          wgmma_rs192(acc, a[4], a[5], a[6], a[7], dsc + kc * 512 + 64, 1);
          wgmma_rs192(acc, a[8], a[9], a[10], a[11], dsc + kc * 512 + 256, 1);
          wgmma_rs192(acc, a[12], a[13], a[14], a[15], dsc + kc * 512 + 320, 1);
          wg_commit();
          const uint8_t* pn = p0 + (kc < 4 ? (kc + 4) * 128 : 128 * DM * 2 + (kc - 4) * 128);
          if (it == 0 && wg == 0) {
#pragma unroll
            for (int i = 0; i < 4; i++) if (kc < 4) lds128r(A[kc] + 4 * i, sb + 196608 + (kc * 4 + i) * 2048 + tid * 16);
          } else if (kc < 4 || it < 15) load_a(A[kc & 3], pn, pn + 8192);
          if (kc == 0) { QSTAMP(it, 1); }
          if (kc == 4) { QSTAMP(it, 4); }
          if (kc == 6 && it == 0 && wg == 0) bar_arrive<1, 256>();
          wg_wait<1>();
        }
        wg_wait<0>();
        QSTAMP(it, 2);
#pragma unroll
        for (int b = 0; b < 2; b++) {
          const float* d = acc + 16 * b;
          *reinterpret_cast<uint4*>(dst + b * 512) = make_uint4(pack_bf16(d[0], d[1]), pack_bf16(d[4], d[5]), pack_bf16(d[8], d[9]), pack_bf16(d[12], d[13]));
          *reinterpret_cast<uint4*>(dst + b * 512 + 2048) = make_uint4(pack_bf16(d[2], d[3]), pack_bf16(d[6], d[7]), pack_bf16(d[10], d[11]), pack_bf16(d[14], d[15]));
        }
#pragma unroll
        for (int b = 0; b < 4; b++) {
          const float* d = acc + 32 + 8 * b;
          *reinterpret_cast<uint4*>(dst + dv + b * 1024) = make_uint4(movm(pack_bf16(d[0], d[1])), movm(pack_bf16(d[4], d[5])), movm(pack_bf16(d[2], d[3])), movm(pack_bf16(d[6], d[7])));
          *reinterpret_cast<uint4*>(dst + dq + b * 512) = make_uint4(pack_bf16(d[32], d[33]), pack_bf16(d[34], d[35]), pack_bf16(d[36], d[37]), pack_bf16(d[38], d[39]));
        }
        publish();
        QSTAMP(it, 3);
        p0 += 128 * DM * 2; dst += (size_t)4 * NH * BLK_BYTES;
        if (it == 0 && wg == 0) {
#pragma unroll
          for (int i = 0; i < 4; i++) load_a(A[i], p0 + i * 128, p0 + i * 128 + 8192);
        }
      }
    }
    GSTAMP(1);
    const uint32_t ea = mapa(sb + GB_EMPTY, lane & 1);
    if (lane < 2 * G_NST) mbar_arrive_cluster(ea + 8 * (lane >> 1));
    const int gc = (cta - 64) >> 1;
    const int jn = args.first[gc + 1];
    int ji = args.first[gc];
    const uint64_t dsc = dsc_hi | (uint64_t)(((sb >> 4) & 0x3FFF) | ((8192 >> 4) << 16));
    uint32_t st = 0, ph = 0;
    bool loaded = false;
    const uint8_t *p0, *p1;
    int ad;
    auto set_a = [&](uint32_t job) {
      const int m16 = ((job >> 1) & 7) * 16 + j * 8 + warp;
      const bool fin = job & 1;
      p0 = fin ? g_a + (size_t)m16 * A_TILE + ((job >> 8) & 127) * 2048 + t * 128 + g * 16
               : reinterpret_cast<const uint8_t*>(args.x) + (size_t)(m16 * 16 + g) * (DM * 2) + t * 16;
      p1 = p0 + (fin ? 512 : 8 * DM * 2);
      ad = fin ? 1024 : 64;
    };
    auto dep_ptr = [&](uint32_t job) { return (((job >> 8) & 127) < 64 ? g_fo : g_fh) + ((job >> 1) & 7) * 16 + j * 8 + warp; };
    auto dep_cnt = [&](uint32_t job) { return tag * (((job >> 8) & 127) < 64 ? 32u : 14u); };
    float acc[128];
    for (; ji < jn; ji++) {
      const uint32_t job = args.job[ji];
      if (!loaded) {
        if (job & 1) wait_count(dep_ptr(job), dep_cnt(job));
        set_a(job);
        load_a(A[0], p0, p1, ad); load_a(A[1], p0 + 2 * ad, p1 + 2 * ad, ad);
      }
      QSTAMP(16 + ji - args.first[gc], 0);
      const uint32_t nxt = args.job[ji + 1];
      const uint32_t dep = ld_relaxed(dep_ptr(nxt));
      const int nk = (job >> 15) & 127;
      uint32_t pst = 0;
      const unsigned* gp = g_gate + (((job >> 1) & 7) * 16 + j * 8 + warp) * 16 + g;
      uint32_t g0 = ld_relaxed(gp), g1 = ld_relaxed(gp + 8);
      if (wg == 1 && nk >= 8) bar_sync<2, 256>();
      for (int k = 0; k < nk; k += 2) {
#pragma unroll
        for (int u = 0; u < 2; u++) {
          uint32_t* a = U[u];
          mbar_wait(sb + GB_FULL + 8 * st, ph);
          frag_a(a, A[u], args.zero);
          const uint64_t d = dsc + st * (G_ST >> 4);
          wg_fence();
          wgmma_rs256(acc, a[0], a[1], a[2], a[3], d, u != 0 || (k | (job & (1u << 24))) != 0);
          wgmma_rs256(acc, a[4], a[5], a[6], a[7], d + 64, 1);
          wgmma_rs256(acc, a[8], a[9], a[10], a[11], d + 256, 1);
          wgmma_rs256(acc, a[12], a[13], a[14], a[15], d + 320, 1);
          wg_commit();
          if (k + 2 < nk) load_a(A[u], p0 + (2 * u + 4) * ad, p1 + (2 * u + 4) * ad, ad);
          if (u == LAG_U && k == LAG_K && wg == 0 && nk >= 8) bar_arrive<2, 256>();
          wg_wait<1>();
          if ((u != 0 || k != 0) && lane < 2) mbar_arrive_cluster(ea + 8 * pst);
          pst = st;
          if (++st == G_NST) { st = 0; ph ^= 1; }
        }
        p0 += 4 * ad; p1 += 4 * ad;
      }
      wg_wait<0>();
      QSTAMP(16 + ji - args.first[gc], 2);
      if (lane < 2) mbar_arrive_cluster(ea + 8 * pst);
      loaded = ji + 1 < jn && (!(nxt & 1) || (int)(dep - dep_cnt(nxt)) >= 0);
      if (loaded) {
        if (nxt & 1) fence_gpu();
        set_a(nxt);
        load_a(A[0], p0, p1, ad); load_a(A[1], p0 + 2 * ad, p1 + 2 * ad, ad);
      }
      QSTAMP(16 + ji - args.first[gc], 1);
      const int m16 = ((job >> 1) & 7) * 16 + j * 8 + warp, n = (job >> 4) & 15;
      const int row = m16 * 16 + g;
      if (!(job & 1)) {
        check_gate(g0, g1, g_gate + row, tag);
        const float s0 = 1.0f - __uint_as_float(g0), s1 = 1.0f - __uint_as_float(g1);
        uint8_t* q = g_a + (size_t)m16 * A_TILE + (HD / 32 + n * 4) * 1024 + t * 128 + g * 16;
#pragma unroll
        for (int b = 0; b < 4; b++) {
          uint32_t lo[4], hi[4];
#pragma unroll
          for (int i = 0; i < 4; i++) {
            const float* ga = acc + 16 * b + 4 * i;
            float v[4];
#pragma unroll
            for (int e = 0; e < 4; e++) v[e] = __fdividef(ga[64 + e] * (e < 2 ? s0 : s1), 1.0f + ex2(ga[e] * -1.4426950408889634f));
            lo[i] = pack_bf16(v[0], v[1]); hi[i] = pack_bf16(v[2], v[3]);
          }
          *reinterpret_cast<uint4*>(q + 1024 * b) = make_uint4(lo[0], lo[1], lo[2], lo[3]);
          *reinterpret_cast<uint4*>(q + 1024 * b + 512) = make_uint4(hi[0], hi[1], hi[2], hi[3]);
        }
        QSTAMP(16 + ji - args.first[gc], 4);
        publish();
      } else {
        const uint32_t mode = (job >> 22) & 3, parts = job >> 25;
        float4* q = reinterpret_cast<float4*>(g_acc) + (m16 * 2 + n) * 1024;
        if (mode == M_STORE) {
#pragma unroll
          for (int i = 0; i < 32; i++) q[i * 32 + lane] = make_float4(acc[4 * i], acc[4 * i + 1], acc[4 * i + 2], acc[4 * i + 3]);
          publish();
        } else if (mode == M_RED) {
          const unsigned* fc = g_fc + m16 * 2 + n;
          wait_count(fc, (tag - 1) * (parts + 1) + 1);
#pragma unroll
          for (int i = 0; i < 32; i++)
            asm volatile("red.relaxed.gpu.global.add.v4.f32 [%0], {%1,%2,%3,%4};"
                         :: "l"(q + i * 32 + lane), "f"(acc[4 * i]), "f"(acc[4 * i + 1]), "f"(acc[4 * i + 2]), "f"(acc[4 * i + 3]) : "memory");
          publish();
          wait_count(fc, tag * (parts + 1));
          for (int r = ((job >> 8) & 63) >> 2, e = r + (nk >> 2); r < e; r++) {
            const int i = (r >> 3) * 16 + (lane >> 1);
            const float4 u = __ldcg(q + i * 32 + (r & 7) * 4 + (lane & 1) * 2), v = __ldcg(q + i * 32 + (r & 7) * 4 + (lane & 1) * 2 + 1);
            uint2* o = reinterpret_cast<uint2*>(args.out + (size_t)(m16 * 16 + (r & 7)) * DM + n * 256 + (r >> 3) * 128) + lane;
            o[0] = make_uint2(pack_bf16(u.x, u.y), pack_bf16(v.x, v.y));
            o[2 * DM] = make_uint2(pack_bf16(u.z, u.w), pack_bf16(v.z, v.w));
          }
        } else if (mode == M_OUT) {
          uint32_t* o = reinterpret_cast<uint32_t*>(args.out + (size_t)row * DM + n * 256) + t;
#pragma unroll
          for (int i = 0; i < 32; i++) { o[4 * i] = pack_bf16(acc[4 * i], acc[4 * i + 1]); o[4 * i + 4 * DM] = pack_bf16(acc[4 * i + 2], acc[4 * i + 3]); }
        }
      }
      GSTAMP(2 + ji - args.first[gc]);
      QSTAMP(16 + ji - args.first[gc], 3);
    }
    asm volatile("barrier.cluster.arrive.aligned; barrier.cluster.wait.aligned;" ::: "memory");
  } else if (cta >= 64) {
    start();
    asm volatile("setmaxnreg.dec.sync.aligned.u32 40;");
    if (warp == 9 && lane == 0 && cta < 128) {
      for (int i = 0; i < 4; i++) {
        mbar_expect_tx(sb + GB_W + 8 * i, 49152);
        for (int b = 1; b < 4; b++) tma5d(sb + (b % 3) * 65536 + i * 16384, &args.pw[b % 3], h * DH + j * 64, 4 * i, sb + GB_W + 8 * i);
      }
    } else if (warp == 8 && lane == 0) {
      const int gc = (cta - 64) >> 1;
      const int jn = args.first[gc + 1];
      uint32_t st = 0, ph = 0;
      for (int ji = args.first[gc]; ji < jn; ji++) {
        const uint32_t job = args.job[ji];
        const int n = (job >> 4) & 15, k0 = (job >> 8) & 127, nk = (job >> 15) & 127;
        const CUtensorMap* tm = &args.pb[(job & 1) ? (k0 < 64 ? 2 : 3) : j];
        const int col = (job & 1) ? n * 256 + j * 128 : n * 128;
        for (int k = 0; k < nk; k++) {
          mbar_wait_cluster(sb + GB_EMPTY + 8 * st, ph);
          const uint32_t mb = sb + GB_FULL + 8 * st, dst = sb + st * G_ST + j * 16384;
          mbar_expect_tx(mb, G_ST);
          tma5d_mc(dst, tm, col, 2 * ((k0 & 63) + k), mb);
          tma5d_mc(dst + 8192, tm, col + 64, 2 * ((k0 & 63) + k), mb);
          if (++st == G_NST) { st = 0; ph ^= 1; }
        }
      }
      atomicAdd(&g_done, 1u);
    } else if (warp > 9) {
      const int wg = warp - 10, gc = (cta - 64) >> 1;
      uint32_t ev = sb + GB_EV + wg * (8 * G_NEV);
      if (cta < 128)
        for (int it = 0; it < 16; it++, ev += 8) {
          mbar_wait(ev, 0);
          fence_gpu();
          if (lane < 4) red_relaxed(g_fq + (4 * it + 2 * wg + (lane >> 1)) * NH + h);
        }
      const int jn = args.first[gc + 1];
      for (int ji = args.first[gc]; ji < jn; ji++) {
        const uint32_t job = args.job[ji], mode = (job >> 22) & 3;
        if ((job & 1) && (mode == M_CONT || mode == M_OUT)) continue;
        const int m16 = ((job >> 1) & 7) * 16 + j * 8 + wg * 4 + (lane & 3);
        mbar_wait(ev, 0);
        ev += 8;
        fence_gpu();
        if (lane < 4) red_relaxed((job & 1) ? g_fc + m16 * 2 + ((job >> 4) & 15) : g_fh + m16);
      }
    }
    __syncwarp();
    asm volatile("barrier.cluster.arrive.aligned; barrier.cluster.wait.aligned;" ::: "memory");
  } else if (warp < 8) {
    const int gam = warp >> 2, w = warp & 3;
    uint32_t wq[16][4], wk[16][4], wv[16][4];
    const uint32_t l16 = __shfl_sync(~0u, lane * 16, lane);
    float fq, fk, fv;
    uint32_t p0[4], p1[4];
    {
      const uint32_t o = ((lane & 7) + ((lane >> 4) << 3)) * 128 + (((2 * w + ((lane >> 3) & 1)) ^ (lane & 7)) << 4) + gam * 16384 + (w << 12);
      auto load_w = [&](uint32_t (*W)[4], uint32_t base) {
        uint32_t m = 0;
#pragma unroll
        for (int i = 0; i < 16; i++) {
          ldm4t(W[i], base + (o ^ ((i >> 2) << 12)) + ((i >> 1) & 1) * 32768 + (i & 1) * 2048);
          m = absmax2(absmax2(m, absmax2(W[i][0], W[i][1])), absmax2(W[i][2], W[i][3]));
        }
        return __reduce_max_sync(~0u, fold_absmax(m));
      };
      auto to_f16 = [&](uint32_t (*W)[4], uint32_t m) {
        const uint32_t e = max(m >> 7, 15u);
        const uint32_t sc = (268u - e) * 0x00800080u;
#pragma unroll
        for (int i = 0; i < 64; i++) {
          uint32_t v;
          asm("mul.rn.bf16x2 %0, %1, %2;" : "=r"(v) : "r"(W[i >> 2][i & 3]), "r"(sc));
          W[i >> 2][i & 3] = pack_f16(bf_lo(v), bf_hi(v));
          asm volatile("" : "+r"(W[i >> 2][i & 3]));
        }
        return __uint_as_float((e - 14u) << 23);
      };
      uint32_t mm = 0;
      {
#pragma unroll
        for (int i = 0; i < 16; i++) *reinterpret_cast<uint4*>(wq[i]) = __ldg(reinterpret_cast<const uint4*>(args.mem0) + i * 32 + lane);
#pragma unroll
        for (int i = 0; i < 4; i++) {
          const uint32_t* mp = reinterpret_cast<const uint32_t*>(args.mem0 + (lane >> 2) * DM + warp * 32 + i * 8 + 2 * (lane & 3));
          p0[i] = __ldg(mp); p1[i] = __ldg(mp + 128);
        }
#pragma unroll
        for (int i = 0; i < 16; i++) mm = absmax2(mm, absmax2(absmax2(wq[i][0], wq[i][1]), absmax2(wq[i][2], wq[i][3])));
      }
      const int E0 = min(max((int)(__reduce_max_sync(~0u, fold_absmax(mm)) >> 7) - 141, -100), 100);
      sts32(sb + C_UP, (uint32_t)(127 + E0) << 23); sts32(sb + C_UP + 4, E0);
      start();
      PSTAMP(0, 2);
      if (tid == 0) {
        const int col = h * DH + j * 64;
        mbar_expect_tx(sb + MB_WV, 65536); mbar_expect_tx(sb + MB_WQ, 65536); mbar_expect_tx(sb + MB_WK, 65536);
        for (int i = 0; i < 4; i++) {
          tma2d(sb + C_WO + i * 16384, &args.tmv, col, i * 128, sb + MB_WV);
          tma2d(sb + C_SW + i * 16384, &args.tmq, col, i * 128, sb + MB_WQ);
          tma2d(sb + C_KVQ + i * 16384, &args.tmk, col, i * 128, sb + MB_WK);
        }
        asm volatile("cp.async.bulk.prefetch.L2.global [%0], 65536;" :: "l"(args.wo + cta * 32768) : "memory");
      }
      __syncwarp();
      const float dn = __uint_as_float((uint32_t)(127 - E0) << 23);
#pragma unroll
      for (int i = 0; i < 4; i++) {
        p0[i] = pack_f16(bf_lo(p0[i]) * dn, bf_hi(p0[i]) * dn);
        p1[i] = pack_f16(bf_lo(p1[i]) * dn, bf_hi(p1[i]) * dn);
      }
      asm volatile("setmaxnreg.inc.sync.aligned.u32 " FAT_REGS ";");
      PSTAMP(0, 3);
      mbar_wait(sb + MB_WV, 0);
      PSTAMP(0, 4);
      const uint32_t mv = load_w(wv, sb + C_WO);
      if (lane == 0) sts32(sb + C_WM + warp * 4, mv);
      bar_arrive<10, 384>();
      fv = to_f16(wv, mv);
      PSTAMP(0, 5);
      mbar_wait(sb + MB_WQ, 0);
      fq = to_f16(wq, load_w(wq, sb + C_SW));
      PSTAMP(0, 6);
      mbar_wait(sb + MB_WK, 0);
      PSTAMP(0, 7);
      const uint32_t mk = load_w(wk, sb + C_KVQ);
      bar_sync<11, 288>();
      fk = to_f16(wk, mk);
#pragma unroll
      for (int i = 0; i < 8; i++) {
        sts128(sb + C_SW + warp * 8192 + i * 1024 + l16, wq[i][0], wq[i][1], wq[i][2], wq[i][3]);
        sts128(sb + C_SW + warp * 8192 + i * 1024 + 512 + l16, wk[i][0], wk[i][1], wk[i][2], wk[i][3]);
      }
      PSTAMP(0, 8);
      mbar_wait(sb + MB_WO, 0);
      PSTAMP(0, 9);
      const uint32_t a = C_WO + (warp >> 1) * 16384 + ((lane & 7) + ((lane >> 4) << 3)) * 128 + ((((warp & 1) * 4 + ((lane >> 3) & 1)) ^ (lane & 7)) << 4);
#pragma unroll
      for (int i = 0; i < 8; i++) { ldm4t(wq[i], sb + a + (i << 11)); ldm4t(wk[i], sb + (a ^ 32) + (i << 11)); }
      bar_sync<13, 320>();
#pragma unroll
      for (int i = 0; i < 8; i++) {
        sts128(sb + C_WO + warp * 8192 + i * 1024 + l16, wq[i][0], wq[i][1], wq[i][2], wq[i][3]);
        sts128(sb + C_WO + warp * 8192 + i * 1024 + 512 + l16, wk[i][0], wk[i][1], wk[i][2], wk[i][3]);
      }
#pragma unroll
      for (int i = 0; i < 8; i++) { lds128r(wq[i], sb + C_SW + warp * 8192 + i * 1024 + l16); lds128r(wk[i], sb + C_SW + warp * 8192 + i * 1024 + 512 + l16); }
    }
    const uint32_t peer = mapa(sb, j ^ 1);
    const uint32_t sw = sb + warp * 8192 - w * 1024, so = sb - w * 1024;
    const uint32_t rw = (uint32_t)(uintptr_t)ring + (w >> 1) * 8192 + (gam ^ (w >> 1)) * 4096 + (w & 1) * 2048, rh = (uint32_t)((uintptr_t)ring >> 32);
    const int delay = POLL_DELAY;
    const uint32_t mb = sb + C_MEM + gam * 4096;
    PSTAMP(0, 10);
    const uint32_t ma = __shfl_sync(~0u, w * 1024 + lane * 16, lane);
    for (int s = 0;; s++) {
      const uint32_t sz = s & args.zero;
      sts128(mb + ma, p0[0], p0[1], p0[2], p0[3]);
      sts128(mb + 512 + ma, p1[0], p1[1], p1[2], p1[3]);
      asm volatile("{ .reg .pred p; setp.ne.u32 p, %0, 0; @p bar.sync 4, 128; @!p bar.sync 3, 128; }" :: "r"(gam) : "memory");
      float cq[4], ck[4], cw[4], cx[4];
      uint32_t b[8][4], Wo[16][4];
      hma16z(ck, wk[0], p0[0], p0[1]);
      hma16z(cq, wq[0], p0[0], p0[1]);
      hma16z(cx, wk[1], p0[2], p0[3]);
      hma16z(cw, wq[1], p0[2], p0[3]);
      ldv_s(b[2], mb + (ma ^ 1024)); ldv_s(b[3], mb + 512 + (ma ^ 1024));
      FENCE_BB;
      hma16(ck, wk[2], p1[0], p1[1]);
      hma16(cq, wq[2], p1[0], p1[1]);
      hma16(cx, wk[3], p1[2], p1[3]);
      hma16(cw, wq[3], p1[2], p1[3]);
#pragma unroll
      for (int i = 4; i < 6; i++) ldv_s(b[i], mb + (i & 1) * 512 + ((ma | sz) ^ ((i >> 1) * 1024)));
      FENCE_BB;
      hma16(ck, wk[4], b[2][0], b[2][1]);
      hma16(cq, wq[4], b[2][0], b[2][1]);
      hma16(cx, wk[5], b[2][2], b[2][3]);
      hma16(cw, wq[5], b[2][2], b[2][3]);
#pragma unroll
      for (int i = 6; i < 8; i++) ldv_s(b[i], mb + (i & 1) * 512 + ((ma | sz) ^ ((i >> 1) * 1024)));
      FENCE_BB;
      uint32_t mx = absmax2h(absmax2h(absmax2h(p0[0], p0[1]), absmax2h(p0[2], p0[3])), absmax2h(absmax2h(p1[0], p1[1]), absmax2h(p1[2], p1[3])));
      mx = __reduce_max_sync(~0u, absmax2h(mx, mx << 16) & 0x7FFFFFFFu);
#pragma unroll
      for (int i = 3; i < WO_AT; i++) {
        hma16(ck, wk[2 * i], b[i][0], b[i][1]);
        hma16(cq, wq[2 * i], b[i][0], b[i][1]);
        hma16(cx, wk[2 * i + 1], b[i][2], b[i][3]);
        hma16(cw, wq[2 * i + 1], b[i][2], b[i][3]);
      }
      const uint32_t lw = ma | (b[5][0] & b[6][0] & b[7][0] & args.zero);
      FENCE_BB;
      const float up = __uint_as_float(lds32(sb + C_UP));
      sts32(sb + C_MX + warp * 4, mx);
#pragma unroll
      for (int u = 0; u < WO_QK; u++) ldv_s(Wo[u], sw + C_WO + u * 512 + lw);
      FENCE_BB;
#pragma unroll
      for (int i = WO_AT; i < 8; i++) {
        hma16(ck, wk[2 * i], b[i][0], b[i][1]);
        hma16(cq, wq[2 * i], b[i][0], b[i][1]);
        hma16(cx, wk[2 * i + 1], b[i][2], b[i][3]);
        hma16(cw, wq[2 * i + 1], b[i][2], b[i][3]);
      }
      const float uq = up * fq, uk = up * fk;
      stm4(sb + C_QM + gam * 512 + lw, pack_bf16((cq[0] + cw[0]) * uq, (cq[1] + cw[1]) * uq), pack_bf16((cq[2] + cw[2]) * uq, (cq[3] + cw[3]) * uq),
           pack_bf16((ck[0] + cx[0]) * uk, (ck[1] + cx[1]) * uk), pack_bf16((ck[2] + cx[2]) * uk, (ck[3] + cx[3]) * uk));
      bar_arrive<6, 384>();
      FENCE_BB;
      hma16z(cq, wv[0], p0[0], p0[1]);
      hma16z(cw, wv[1], p0[2], p0[3]);
      hma16z(ck, wv[2], p1[0], p1[1]);
      hma16z(cx, wv[3], p1[2], p1[3]);
#pragma unroll
      for (int i = 2; i < 8; i += 2) {
        hma16(cq, wv[2 * i], b[i][0], b[i][1]);
        hma16(cw, wv[2 * i + 1], b[i][2], b[i][3]);
        hma16(ck, wv[2 * i + 2], b[i + 1][0], b[i + 1][1]);
        hma16(cx, wv[2 * i + 3], b[i + 1][2], b[i + 1][3]);
      }
      {
        const float uv = up * fv;
        const uint32_t lo = pack_bf16(((cq[0] + cw[0]) + (ck[0] + cx[0])) * uv, ((cq[1] + cw[1]) + (ck[1] + cx[1])) * uv);
        const uint32_t hi = pack_bf16(((cq[2] + cw[2]) + (ck[2] + cx[2])) * uv, ((cq[3] + cw[3]) + (ck[3] + cx[3])) * uv);
        const uint32_t a = C_VM + (s & 1) * 4096 + j * 2048 + gam * 256 + (lw >> 1);
        st_async64(peer + a, lo, hi, peer + MB_V);
        sts64(sb + a, lo, hi);
        __syncwarp();
        asm volatile("{ .reg .pred p; setp.eq.u32 p, %1, 0; @p mbarrier.arrive.shared::cta.b64 _, [%0]; }" :: "r"(sb + MB_V), "r"(ma & 0x1F0) : "memory");
      }
      if (s == NSEG - 1) break;
#pragma unroll
      for (int u = WO_QK; u < WO_EARLY; u++)
        ldv_s(Wo[u], sw + C_WO + u * 512 + (ma | (u >= WO_QK + WO_PAR ? Wo[u - WO_PAR][0] & args.zero : 0u)));
      const uint32_t lb = ma | sz;
      const uint32_t rp = rw + (s & 7) * RING_SLOT;
      const uint32_t o16 = fresh(rp + j * 16384 + (lb & 0x70) + (lb & 0x80) * 2 + (lb & 0x100) * 4);
      const uint32_t o4 = fresh(rp + 128 + ((lb >> 3) & 0x1C) + (lb & 0x100) * 4 + ((~lb & 16) << 10));
      const uint32_t sa = fresh(lb & 0x30);
      FENCE_BB;
      bar_sync<7, 384>();
      ldm4t(b[0], so + C_OT + ma); ldm4t(b[1], so + C_OT + 512 + ma);
      const float2 su = lds64f(sb + C_SU + sa);
      ldm4t(b[2], so + C_OT + 1024 + ma);
      FENCE_BB;
      mma16z(cx, Wo[3][0], Wo[3][1], Wo[3][2], Wo[3][3], b[0][2], b[0][3]);
      mma16z(ck, Wo[1][0], Wo[1][1], Wo[1][2], Wo[1][3], b[0][0], b[0][1]);
      mma16z(cw, Wo[2][0], Wo[2][1], Wo[2][2], Wo[2][3], b[0][2], b[0][3]);
      mma16z(cq, Wo[0][0], Wo[0][1], Wo[0][2], Wo[0][3], b[0][0], b[0][1]);
      FENCE_BB;
      ldm4t(b[3], so + C_OT + 1536 + ma);
      const float r0 = rcp(su.x), r1 = rcp(su.y);
      const uint32_t sel = ((o16 ^ o4) & 16384) ? 0x3210 : 0x5410;
      Wo[12][0] |= __float_as_uint(r0) & __float_as_uint(r1) & sel & args.zero;
#pragma unroll
      for (int k = 1; k < 4; k++) {
        mma16(cq, Wo[4 * k][0], Wo[4 * k][1], Wo[4 * k][2], Wo[4 * k][3], b[k][0], b[k][1]);
        mma16(ck, Wo[4 * k + 1][0], Wo[4 * k + 1][1], Wo[4 * k + 1][2], Wo[4 * k + 1][3], b[k][0], b[k][1]);
        mma16(cw, Wo[4 * k + 2][0], Wo[4 * k + 2][1], Wo[4 * k + 2][2], Wo[4 * k + 2][3], b[k][2], b[k][3]);
        mma16(cx, Wo[4 * k + 3][0], Wo[4 * k + 3][1], Wo[4 * k + 3][2], Wo[4 * k + 3][3], b[k][2], b[k][3]);
      }
      {
        const uint32_t u3 = movm(pack_f16((ck[2] + cx[2]) * r0, (ck[3] + cx[3]) * r1));
        const uint32_t u0 = movm(pack_f16((cq[0] + cw[0]) * r0, (cq[1] + cw[1]) * r1)), u1 = movm(pack_f16((cq[2] + cw[2]) * r0, (cq[3] + cw[3]) * r1));
        const uint32_t u2 = movm(pack_f16((ck[0] + cx[0]) * r0, (ck[1] + cx[1]) * r1));
        asm volatile("red.relaxed.gpu.global.add.noftz.v4.f16x2 [%0], {%1,%2,%3,%4};"
                     :: "l"(gptr(o16, rh)), "r"(u0), "r"(u1), "r"(u2), "r"(__byte_perm(u3, 0x3C00u, sel)) : "memory");
        asm volatile("{ .reg .pred p; setp.eq.u32 p, %2, 0x5410; @p red.relaxed.gpu.global.add.noftz.f16x2 [%0], %1; }"
                     :: "l"(gptr(o4, rh)), "r"(__byte_perm(u3, 0x3C00u, 0x5432)), "r"(sel) : "memory");
      }
      bar_arrive<9, 384>();
      uint32_t z = 0;
#pragma unroll
      for (int i = 0; i < WV_A; i++) {
        uint32_t* d = (i & 1) ? wk[i >> 1] : wq[i >> 1];
        ldv_s(d, sw + C_SW + i * 512 + (ma | z));
        z = d[0] & args.zero;
      }
#pragma unroll 1
      for (int i = 0; i < delay; i++) z = __shfl_sync(~0u, z, 0);
      const uint8_t* const pa = gptr((o16 & ~16384u) | z, rh);
      uint4 a0 = ldv128(pa), a1 = ldv128(pa + 16384);
      uint32_t b0 = ldv32(gptr(o4, rh));
#pragma unroll
      for (int i = WV_A; i < 16; i++) ldv_s((i & 1) ? wk[i >> 1] : wq[i >> 1], sw + C_SW + i * 512 + ma);
      const bool odd = (o4 & 16384) == 0;
      const uint32_t sel0 = fresh(odd ? 0x5410 : 0x3210), sel1 = fresh(sel0 ^ 0x6600);
      FENCE_BB;
      if (__builtin_expect(__any_sync(~0u, (~((odd ? a0.w : a1.w) & b0) & 0x50000000u) != 0), 0)) {
        int it = 0;
        do {
          a0 = ldv128(pa); a1 = ldv128(pa + 16384); b0 = ldv32(gptr(o4, rh));
        } while (__any_sync(~0u, (~((odd ? a0.w : a1.w) & b0) & 0x50000000u) != 0) && ++it < 65536);
      }
      p0[0] = a0.x; p0[1] = a0.y; p0[2] = a0.z; p0[3] = prmt(a0.w, b0, sel0);
      p1[0] = a1.x; p1[1] = a1.y; p1[2] = a1.z; p1[3] = prmt(a1.w, b0, sel1);
    }
    bar_arrive<7, 384>();
    bar_arrive<9, 384>();
  } else {
    const int w = warp - 8, at = tid - 256;
    uint32_t tag;
    {
      uint32_t mx = 0, gw[8], a[8][8];
      float acc[8];
      const int tok = cta * SEGL + w * 8;
      const uint8_t* xr = reinterpret_cast<const uint8_t*>(args.x + (size_t)tok * DM) + lane * 16;
#pragma unroll
      for (int r = 0; r < 8; r++) { ldg128(a[r], xr + r * 1024); ldg128(a[r] + 4, xr + r * 1024 + 512); }
      ldg128(gw, reinterpret_cast<const uint8_t*>(args.gate_w) + lane * 16); ldg128(gw + 4, reinterpret_cast<const uint8_t*>(args.gate_w) + 512 + lane * 16);
#pragma unroll
      for (int r = 0; r < 8; r++) {
        acc[r] = 0.f;
#pragma unroll
        for (int i = 0; i < 8; i++) { acc[r] += bf_lo(a[r][i]) * bf_lo(gw[i]) + bf_hi(a[r][i]) * bf_hi(gw[i]); mx = absmax2(mx, a[r][i]); }
      }
      mx = __reduce_max_sync(~0u, fold_absmax(mx));
      sts32(sb + C_WM + 64 + w * 4, mx);
      tag = start();
      asm volatile("setmaxnreg.dec.sync.aligned.u32 " AUX_REGS ";"
                   : "+f"(acc[0]), "+f"(acc[1]), "+f"(acc[2]), "+f"(acc[3]), "+f"(acc[4]), "+f"(acc[5]), "+f"(acc[6]), "+f"(acc[7]));
#pragma unroll
      for (int o = 16; o; o >>= 1)
#pragma unroll
        for (int r = 0; r < 8; r++) acc[r] += __shfl_xor_sync(~0u, acc[r], o);
#pragma unroll
      for (int r = 1; r < 8; r++) acc[0] = lane == r ? acc[r] : acc[0];
      if (lane < 8) st_relaxed(g_gate + tok + lane, (__float_as_uint(__fdividef(1.0f, 1.0f + __expf(-acc[0]))) & ~15u) | (tag & 15));
    }
    PSTAMP(320, 1);
    bar_sync<10, 384>();
    if (w < 2) {
      if (at == 0) {
        mbar_expect_tx(sb + MB_WO, 65536);
        for (int i = 0; i < 4; i++) tma2d(sb + C_WO + i * 16384, &args.tmo, j * 256 + i * 64, h * DH, sb + MB_WO);
      }
      __syncwarp();
      mbar_wait(sb + MB_WO, 0);
      uint32_t mo = 0;
#pragma unroll 8
      for (int i = 0; i < 64; i++) { const uint4 a = lds128(sb + C_WO + i * 1024 + at * 16); mo = absmax2(mo, absmax2(absmax2(a.x, a.y), absmax2(a.z, a.w))); }
      bar_arrive<13, 320>();
      sts32(sb + C_WM + 32 + w * 4, __reduce_max_sync(~0u, fold_absmax(mo)));
      bar_sync<12, 64>();
      if (at == 0) {
        const uint4 a = lds128(sb + C_WM), b = lds128(sb + C_WM + 16), c = lds128(sb + C_WM + 64);
        const uint2 d = lds64(sb + C_WM + 32);
        asm volatile("st.volatile.global.v4.u32 [%0], {%1,%2,%3,%4};" :: "l"(&g_pub[cta]), "r"(tag), "r"(max(max(c.x, c.y), max(c.z, c.w)) >> 7),
                     "r"(max(max(max(a.x, a.y), max(a.z, a.w)), max(max(b.x, b.y), max(b.z, b.w))) >> 7), "r"(max(d.x, d.y) >> 7) : "memory");
      }
    } else if (w == 2) {
      uint4 r0, r1;
      int it = 0;
      while (true) {
        r0 = ldv128(&g_pub[lane]); r1 = ldv128(&g_pub[lane + 32]);
        if (__all_sync(~0u, r0.x == tag && r1.x == tag)) break;
        if (give_up(++it, 4)) break;
      }
      PSTAMP(320, 11);
      sts32(sb + C_XE + lane * 4, r0.y); sts32(sb + C_XE + 128 + lane * 4, r1.y);
      sts32(sb + C_WE, __reduce_max_sync(~0u, max(r0.z, r1.z)) + __reduce_max_sync(~0u, max(r0.w, r1.w)) - 3 * 126 + 21 - 14);
    } else {
      bar_sync<11, 288>();
      wait_count(g_fq + (lane & 1) * NH + h, tag * 4);
      asm volatile("fence.proxy.async.global;" ::: "memory");
      if (lane == 0) { issue_stage(0, 0); issue_stage(1, 1); }
    }
    __syncwarp();
    const uint32_t peer = mapa(sb, j ^ 1);
    const float SC = 0.08838834764831845f * 1.4426950408889634f;
    const uint32_t ONE = 0x3F803F80u;
    int st = 0, stp = 0;
    PSTAMP(352, 12);
    int E = (int)lds32(sb + C_UP + 4);
    for (int s = 0; s < NSEG; s++) {
      const uint32_t l16 = fresh(lane) * 16;
      const uint32_t kv = sb + C_KVQ + st * KVQ_ST + (j ? 0 : 4096), qx = sb + C_KVQ + st * KVQ_ST + (j ? 16384 : 0);
      uint32_t fq = 0;
      if (w == 3) fq = ld_relaxed(g_fq + min(s + 2, NSEG - 1) * NH + h + (lane & args.zero));
      mbar_wait1(sb + MB_KVQ + 8 * st, stp);
      if (s == 0) { PSTAMP(352, 13); }
      if (s == 1) { PSTAMP(352, 14); }
      uint32_t va[4][4], vm[2][4], ks0, ks1;
      uint32_t vm_a = C_VM + (s & 1) * 4096 + w * 1024 + (l16 >> 1);
      {
        uint32_t ka[4], kc[4], kb[2][4], q[4][4], kk[4];
        lds128r(ka, kv + w * 2048 + j * 1024 + (w >> 1) * 512 + l16);
        lds128r(kc, kv + w * 2048 + j * 1024 + 512 - (w >> 1) * 512 + l16);
#pragma unroll
        for (int i = 0; i < 4; i++) lds128r(va[i], kv + 8192 + w * 2048 + i * 512 + l16);
#pragma unroll
        for (int i = 0; i < 4; i++) {
          kb[0][i] = (w & 1) ? ka[i ^ 2] : ka[i]; kb[1][i] = (w & 1) ? kc[i ^ 2] : kc[i];
          asm volatile("" : "+r"(kb[0][i]), "+r"(kb[1][i]));
        }
        uint32_t q_a = w * 512 + l16, r_a = peer + C_SR + (q_a >> 1);
        uint32_t q_0 = w * 1024 + (l16 & 0x70) + (l16 & 0x80) * 4 + ((l16 >> 1) & 0x80), q_1 = q_0 ^ 1024, q_2 = q_0 ^ 2048, q_3 = q_0 ^ 3072;
        asm volatile("" : "+r"(q_0), "+r"(q_1), "+r"(q_2), "+r"(q_3), "+r"(r_a), "+r"(vm_a));
        FENCE_BB;
        bar_sync<6, 384>();
        float s0[4], s1[4], s2[4];
        ldm4t(q[0], sb + C_QM + q_0); ldm4t(q[1], sb + C_QM + q_1); ldm4t(kk, sb + C_QM + 256 + q_0); ldm4t(q[2], sb + C_QM + q_2); ldm4t(q[3], sb + C_QM + q_3);
        FENCE_BB;
        mma16z(s0, q[0][0], q[0][1], q[0][2], q[0][3], kb[0][0], kb[0][1]);
        mma16z(s1, q[1][0], q[1][1], q[1][2], q[1][3], kb[0][2], kb[0][3]);
        ks0 = hadd2(kk[0], kk[1]); ks1 = hadd2(kk[2], kk[3]);
        mma16z(s2, q[0][0], q[0][1], q[0][2], q[0][3], ks0, ks1);
        mma16(s0, q[2][0], q[2][1], q[2][2], q[2][3], kb[1][0], kb[1][1]);
        mma16(s1, q[3][0], q[3][1], q[3][2], q[3][3], kb[1][2], kb[1][3]);
        const float x2 = s2[0] + s2[2], x3 = s2[1] + s2[3];
        const float x0 = (s0[0] + s0[2]) + (s1[0] + s1[2]), x1 = (s0[1] + s0[3]) + (s1[1] + s1[3]);
        st_async64(r_a, pack_bf16(x0, x1), pack_bf16(x2, x3), peer + MB_S);
        FENCE_BB;
        sts128(sb + C_SL + q_a, __float_as_uint(x0), __float_as_uint(x1), __float_as_uint(x2), __float_as_uint(x3));
        const uint4 ma = lds128(sb + C_MX), mc = lds128(sb + C_MX + 16);
        const int xe = lds32(sb + C_XE + s * 4), we = lds32(sb + C_WE);
        bar_sync<8, 128>();
        float4 u[4];
#pragma unroll
        for (int i = 0; i < 4; i++) u[i] = lds128f(sb + C_SL + i * 512 + l16);
        const bool s_ok = mbar_try(sb + MB_S, s & 1);
        FENCE_BB;
        E = max((int)(max(max(max(ma.x, ma.y), max(ma.z, ma.w)), max(max(mc.x, mc.y), max(mc.z, mc.w))) >> 26) + 112 + E, xe) + we;
        E = min(max(E, -100), 100);
        float up = __uint_as_float((uint32_t)(127 + E) << 23);
        sts32(sb + C_UP, __float_as_uint(up));
        float z0 = (u[0].z + u[1].z) + (u[2].z + u[3].z), z1 = (u[0].w + u[1].w) + (u[2].w + u[3].w);
        asm volatile("" : "+f"(z0), "+f"(z1), "+f"(up));
        if (__builtin_expect(!s_ok, 0)) mbar_wait1(sb + MB_S, s & 1);
        uint2 r[4];
#pragma unroll
        for (int i = 0; i < 4; i++) r[i] = lds64(sb + C_SR + i * 256 + (l16 >> 1));
        const bool v_ok = mbar_try(sb + MB_V, s & 1);
        FENCE_BB;
        const uint32_t rm = hadd2(hadd2(r[0].y, r[1].y), hadd2(r[2].y, r[3].y));
        const float sv[10] = {u[0].x + bf_lo(r[0].x), u[0].y + bf_hi(r[0].x), u[1].x + bf_lo(r[1].x), u[1].y + bf_hi(r[1].x),
                              u[2].x + bf_lo(r[2].x), u[2].y + bf_hi(r[2].x), u[3].x + bf_lo(r[3].x), u[3].y + bf_hi(r[3].x),
                              z0 + bf_lo(rm), z1 + bf_hi(rm)};
        float m = fmaxf(fmaxf(fmaxf(sv[0], sv[1]), fmaxf(sv[2], sv[3])), fmaxf(fmaxf(sv[4], sv[5]), fmaxf(sv[6], sv[7])));
        m = fmaxf(m, fmaxf(sv[8], sv[9])) * SC;
        const float m1 = __shfl_xor_sync(~0u, m, 1), m2 = __shfl_xor_sync(~0u, m, 2), m3 = __shfl_xor_sync(~0u, m, 3);
        float e[10], o0[4], o1[4], o2[4], o3[4], su[4];
#pragma unroll
        for (int i = 0; i < 4; i++) e[i] = ex2v(fmaf(sv[i], SC, -m));
        FENCE_BB;
        const float c = ex2v(m - fmaxf(fmaxf(m, m1), fmaxf(m2, m3)));
#pragma unroll
        for (int i = 4; i < 10; i++) e[i] = ex2v(fmaf(sv[i], SC, -m));
        if (__builtin_expect(!v_ok, 0)) mbar_wait1(sb + MB_V, s & 1);
        lds64r(vm[0], sb + vm_a); lds64r(vm[0] + 2, sb + vm_a + 256); lds64r(vm[1], sb + vm_a + 512); lds64r(vm[1] + 2, sb + vm_a + 768);
        {
          const uint32_t pa = pack_bf16(e[0] * c, e[1] * c), pb = pack_bf16(e[2] * c, e[3] * c);
          const uint32_t pc = pack_bf16(e[4] * c, e[5] * c), pd = pack_bf16(e[6] * c, e[7] * c), pe = pack_bf16(e[8] * c, e[9] * c);
          mma16z(o0, va[0][0], va[0][1], va[0][2], va[0][3], pa, pb);
          mma16z(o1, va[2][0], va[2][1], va[2][2], va[2][3], pa, pb);
          mma16z(su, ONE, ONE, ONE, ONE, pa, pb);
          mma16z(o2, va[1][0], va[1][1], va[1][2], va[1][3], pc, pd);
          mma16z(o3, va[3][0], va[3][1], va[3][2], va[3][3], pc, pd);
          mma16(o0, vm[0][0], vm[0][1], vm[0][2], vm[0][3], pe, pe);
          mma16(o1, vm[1][0], vm[1][1], vm[1][2], vm[1][3], pe, pe);
          mma16(su, ONE, ONE, ONE, ONE, pc, pd);
          mma8(su, ONE, ONE, pe);
#pragma unroll
          for (int i = 0; i < 4; i++) { o0[i] += o2[i]; o1[i] += o3[i]; }
        }
        stm4(sb + C_OT + q_a, pack_bf16(o0[0], o0[1]), pack_bf16(o0[2], o0[3]), pack_bf16(o1[0], o1[1]), pack_bf16(o1[2], o1[3]));
        asm volatile("{ .reg .pred p; setp.lt.u32 p, %3, 64; @p st.shared.v2.f32 [%0], {%1,%2}; }"
                     :: "r"(sb + C_SU + q_a), "f"(su[0] * up), "f"(su[1] * up), "r"(q_a) : "memory");
        bar_arrive<7, 384>();
        FENCE_BB;
        st_async64(r_a + (C_KX - C_SR) + j * 1024, ks0, ks1, peer + MB_K);
        sts64(sb + C_KX + j * 1024 + (q_a >> 1), ks0, ks1);
      }
      if (w == 0) {
        uint32_t g0 = ld_relaxed(g_gate + s * SEGL + 16 * j + (l16 >> 6)), g1 = ld_relaxed(g_gate + s * SEGL + 16 * j + 8 + (l16 >> 6));
        bar_sync<9, 384>();
        float sc[5][4];
#pragma unroll
        for (int i = 0; i < 4; i++) {
          uint32_t a[4], c[4], kb[4][4], km[4];
          lds128r(a, qx + i * 1024 + l16);
          lds128r(kb[0], kv + i * 512 + l16); lds128r(kb[1], kv + 2048 + i * 512 + l16);
          lds128r(c, qx + i * 1024 + 512 + l16);
          lds128r(kb[2], kv + 4096 + i * 512 + l16); lds128r(kb[3], kv + 6144 + i * 512 + l16);
          if (i == 0) mbar_wait1(sb + MB_K, s & 1);
          lds64r(km, sb + C_KX + i * 512 + (l16 >> 1)); lds64r(km + 2, sb + C_KX + i * 512 + 256 + (l16 >> 1));
#pragma unroll
          for (int n = 0; n < 4; n++) {
            if (i == 0) mma16z(sc[n], a[0], a[1], a[2], a[3], kb[n][0], kb[n][1]);
            else mma16(sc[n], a[0], a[1], a[2], a[3], kb[n][0], kb[n][1]);
          }
          if (i == 0) mma16z(sc[4], a[0], a[1], a[2], a[3], km[0], km[1]);
          else mma16(sc[4], a[0], a[1], a[2], a[3], km[0], km[1]);
#pragma unroll
          for (int n = 0; n < 4; n++) mma16(sc[n], c[0], c[1], c[2], c[3], kb[n][2], kb[n][3]);
          mma16(sc[4], c[0], c[1], c[2], c[3], km[2], km[3]);
        }
        if (l16 == 0 && s < NSEG - 1) mbar_expect_tx(sb + MB_K, 1024);
        const float NEG = -1.0e9f * 1.4426950408889634f;
        const int d = 16 * j + (int)(l16 >> 6) - (int)((l16 >> 3) & 6);
#pragma unroll
        for (int n = 0; n < 4; n++) {
          sc[n][0] = d >= 8 * n ? sc[n][0] * SC : NEG; sc[n][1] = d >= 8 * n + 1 ? sc[n][1] * SC : NEG;
          sc[n][2] = d >= 8 * n - 8 ? sc[n][2] * SC : NEG; sc[n][3] = d >= 8 * n - 7 ? sc[n][3] * SC : NEG;
        }
#pragma unroll
        for (int e = 0; e < 4; e++) sc[4][e] *= SC;
        float x0 = fmaxf(sc[0][0], sc[0][1]), x1 = fmaxf(sc[0][2], sc[0][3]);
#pragma unroll
        for (int n = 1; n < 5; n++) { x0 = fmaxf(x0, fmaxf(sc[n][0], sc[n][1])); x1 = fmaxf(x1, fmaxf(sc[n][2], sc[n][3])); }
        x0 = fmaxf(x0, __shfl_xor_sync(~0u, x0, 1)); x1 = fmaxf(x1, __shfl_xor_sync(~0u, x1, 1));
        x0 = fmaxf(x0, __shfl_xor_sync(~0u, x0, 2)); x1 = fmaxf(x1, __shfl_xor_sync(~0u, x1, 2));
        float y0 = 0.f, y1 = 0.f;
#pragma unroll
        for (int n = 0; n < 5; n++) {
          sc[n][0] = ex2(sc[n][0] - x0); sc[n][1] = ex2(sc[n][1] - x0); sc[n][2] = ex2(sc[n][2] - x1); sc[n][3] = ex2(sc[n][3] - x1);
          y0 += sc[n][0] + sc[n][1]; y1 += sc[n][2] + sc[n][3];
        }
        y0 += __shfl_xor_sync(~0u, y0, 1); y1 += __shfl_xor_sync(~0u, y1, 1);
        y0 += __shfl_xor_sync(~0u, y0, 2); y1 += __shfl_xor_sync(~0u, y1, 2);
        check_gate(g0, g1, g_gate + s * SEGL + 16 * j + (l16 >> 6), tag);
        const float r0 = rcp(y0) * __uint_as_float(g0), r1 = rcp(y1) * __uint_as_float(g1);
        sts128(kv + l16, pack_bf16(sc[0][0] * r0, sc[0][1] * r0), pack_bf16(sc[1][0] * r0, sc[1][1] * r0),
               pack_bf16(sc[2][0] * r0, sc[2][1] * r0), pack_bf16(sc[3][0] * r0, sc[3][1] * r0));
        sts128(kv + 512 + l16, pack_bf16(sc[0][2] * r1, sc[0][3] * r1), pack_bf16(sc[1][2] * r1, sc[1][3] * r1),
               pack_bf16(sc[2][2] * r1, sc[2][3] * r1), pack_bf16(sc[3][2] * r1, sc[3][3] * r1));
        sts64(kv + 1024 + (l16 >> 1), pack_bf16(sc[4][0] * r0, sc[4][1] * r0), pack_bf16(sc[4][2] * r1, sc[4][3] * r1));
#pragma unroll
        for (int i = 0; i < 4; i++) lds128r(va[i], kv + 8192 + i * 512 + l16);
        lds64r(vm[0], sb + vm_a); lds64r(vm[0] + 2, sb + vm_a + 256); lds64r(vm[1], sb + vm_a + 512); lds64r(vm[1] + 2, sb + vm_a + 768);
      } else {
        bar_arrive<9, 384>();
        if (w == 3) {
          if (lane == 0) {
            asm volatile("cp.async.bulk.wait_group 0;" ::: "memory");
            if (s > 0) FLAG_O(g_fo + 2 * (s - 1) + j);
            if (s + 2 < NSEG) {
              int it = 0;
              while ((int)(fq - tag * 4) < 0) { if (give_up(++it, 5)) break; fq = ld_acquire(g_fq + (s + 2) * NH + h); }
              asm volatile("fence.proxy.async.global;" ::: "memory");
              issue_stage(s + 2, st ? st - 1 : 2);
            }
          }
        } else if (w == 2) {
          if (lane == 0 && s < NSEG - 1) { mbar_expect_tx(sb + MB_S, TX_S); mbar_expect_tx(sb + MB_V, TX_V); }
        } else {
          if (lane < 10) asm volatile("st.global.v4.u32 [%0], {%1,%1,%1,%1};" :: "l"(ring + ((s - 2) & 7) * RING_SLOT + (cta >> 1) * 1024 + j * 256 + lane * 16), "r"(0) : "memory");
        }
        __syncwarp();
      }
      bar_sync<8, 128>();
      {
        uint32_t p[2][4], p4[2];
        lds128r(p[0], kv + l16); lds128r(p[1], kv + 512 + l16); lds64r(p4, kv + 1024 + (l16 >> 1));
        float o[4][4];
#pragma unroll
        for (int i = 0; i < 4; i++) mma16z(o[i], va[(i & 1) * 2][0], va[(i & 1) * 2][1], va[(i & 1) * 2][2], va[(i & 1) * 2][3], p[i >> 1][0], p[i >> 1][1]);
#pragma unroll
        for (int i = 0; i < 4; i++) mma16(o[i], va[(i & 1) * 2 + 1][0], va[(i & 1) * 2 + 1][1], va[(i & 1) * 2 + 1][2], va[(i & 1) * 2 + 1][3], p[i >> 1][2], p[i >> 1][3]);
#pragma unroll
        for (int i = 0; i < 4; i++) mma16(o[i], vm[i & 1][0], vm[i & 1][1], vm[i & 1][2], vm[i & 1][3], p4[i >> 1], p4[i >> 1]);
#pragma unroll
        for (int i = 0; i < 2; i++)
          stm4t(qx + w * 1024 + i * 512 + l16, pack_bf16(o[2 * i][0], o[2 * i][1]), pack_bf16(o[2 * i][2], o[2 * i][3]),
                pack_bf16(o[2 * i + 1][0], o[2 * i + 1][1]), pack_bf16(o[2 * i + 1][2], o[2 * i + 1][3]));
        asm volatile("fence.proxy.async.shared::cta;" ::: "memory");
      }
      if (w == 3) {
        bar_sync<5, 128>();
        if (lane == 0) {
          asm volatile("cp.async.bulk.global.shared::cta.bulk_group [%0], [%1], 4096;" :: "l"(g_a + (size_t)(2 * s + j) * A_TILE + h * 4096), "r"(qx) : "memory");
          asm volatile("cp.async.bulk.commit_group;" ::: "memory");
        }
        __syncwarp();
      } else {
        bar_arrive<5, 128>();
      }
      if (++st == 3) { st = 0; stp ^= 1; }
    }
    if (w == 3 && lane == 0) {
      asm volatile("cp.async.bulk.wait_group 0;" ::: "memory");
      FLAG_O(g_fo + 2 * (NSEG - 1) + j);
    }
    if (w == 0 && lane == 0) atomicAdd(&g_done, 1u);
  }
}

typedef CUresult (*EncodeFn)(CUtensorMap*, CUtensorMapDataType, cuuint32_t, void*, const cuuint64_t*, const cuuint64_t*, const cuuint32_t*,
                             const cuuint32_t*, CUtensorMapInterleave, CUtensorMapSwizzle, CUtensorMapL2promotion, CUtensorMapFloatOOBfill);
static void make_map(EncodeFn enc, CUtensorMap* tm, const void* base, uint64_t cols, uint64_t rows, uint32_t bc, uint32_t br) {
  cuuint64_t dims[2] = {cols, rows};
  cuuint64_t strides[1] = {cols * 2};
  cuuint32_t box[2] = {bc, br}, es[2] = {1, 1};
  enc(tm, CU_TENSOR_MAP_DATA_TYPE_BFLOAT16, 2, const_cast<void*>(base), dims, strides, box, es, CU_TENSOR_MAP_INTERLEAVE_NONE,
      CU_TENSOR_MAP_SWIZZLE_128B, CU_TENSOR_MAP_L2_PROMOTION_L2_256B, CU_TENSOR_MAP_FLOAT_OOB_FILL_NONE);
}

static int make_map5(EncodeFn enc, CUtensorMap* tm, const void* base, uint64_t cols, uint64_t rows, uint32_t groups, bool regroup) {
  const uint64_t rb = cols * 2;
  cuuint64_t dims[5] = {cols, 2, 4, 4, rows / 32};
  cuuint64_t strides[4] = {rb, (regroup ? 8 : 2) * rb, (regroup ? 2 : 8) * rb, 32 * rb};
  cuuint32_t box[5] = {64, 2, 4, 4, groups}, es[5] = {1, 1, 1, 1, 1};
  return (int)enc(tm, CU_TENSOR_MAP_DATA_TYPE_BFLOAT16, 5, const_cast<void*>(base), dims, strides, box, es, CU_TENSOR_MAP_INTERLEAVE_NONE,
                  CU_TENSOR_MAP_SWIZZLE_128B, CU_TENSOR_MAP_L2_PROMOTION_L2_256B, CU_TENSOR_MAP_FLOAT_OOB_FILL_NONE);
}

static void build_schedule(Args& a) {
  static uint32_t lists[NGC][48];
  int cnt[NGC] = {}, nglu[NGC];
  auto fin = [](int p, int n, int k0, int nk, uint32_t mode, int keep, int parts) {
    return (uint32_t)(1 | p << 1 | n << 4 | k0 << 8 | nk << 15) | mode << 22 | (uint32_t)keep << 24 | (uint32_t)parts << 25;
  };
  const int early = GLU_EARLY, order[8] = {3, 4, 5, 6, 7, 0, 1, 2};
  int left = 112 - 2 * early;
  for (int c = 0; c < NGC; c++) { nglu[c] = c < 8 ? 0 : 3; left -= nglu[c]; }
  for (int c = 31; left > 0; c--, left--) nglu[c]++;
  int g = 0;
  auto glu = [&](int c) { lists[c][cnt[c]++] = (uint32_t)(order[g / 14] << 1 | (g % 14) << 4 | 8 << 15); g++; };
  for (int i = 0; i < early; i++) { glu(32); glu(33); }
  for (int r = 0; r < 8; r++) for (int c = NGC - 1; c >= 0; c--) if (r < nglu[c] && g < 112) glu(c);
  for (int c = 0; c < 6; c++) { lists[c][cnt[c]++] = fin(c >> 1, c & 1, 0, 64, M_CONT, 0, 0); lists[c][cnt[c]++] = fin(c >> 1, c & 1, 64, 28, M_OUT, 1, 0); }
  for (int c = 6; c < 8; c++) { lists[c][cnt[c]++] = fin(3, c & 1, 64, 28, M_CONT, 0, 0); lists[c][cnt[c]++] = fin(3, c & 1, 0, 64, M_OUT, 1, 0); }
  for (int c = 8; c < 16; c++) lists[c][cnt[c]++] = fin(c >> 1, c & 1, 64, 28, M_STORE, 0, 0);
  for (int c = 16; c < 20; c++) lists[c][cnt[c]++] = fin(4, c & 1, ((c - 16) >> 1) * 32, 32, M_RED, 0, 2);
  for (int c = 20; c < 24; c++) lists[c][cnt[c]++] = fin(5, c & 1, ((c - 20) >> 1) * 32, 32, M_RED, 0, 2);
  for (int c = 8, q = 0; c < 32; c++) if (c < 16 || c >= 24) { lists[c][cnt[c]++] = fin(6, q & 1, (q >> 1) * 8, 8, M_RED, 0, 8); q++; }
  for (int c = 0, q = 0; c < NGC; c++) if (c != 6 && c != 7) { lists[c][cnt[c]++] = fin(7, q & 1, (q >> 1) * 4, 4, M_RED, 0, 16); q++; }
  int o = 0;
  for (int c = 0; c < NGC; c++) { a.first[c] = (uint16_t)o; for (int i = 0; i < cnt[c]; i++) a.job[o++] = lists[c][i]; }
  a.first[NGC] = (uint16_t)o; a.first[NGC + 1] = 0; a.zero = 0;
  for (; o < MAXJOBS; o++) a.job[o] = 0;
}

extern "C" void kernel_launch(void* const* d_in, const int* in_sizes, int n_in, void* d_out, int out_size) {
  (void)in_sizes; (void)n_in; (void)out_size;
  const bf16 *wq = (const bf16*)d_in[2], *wk = (const bf16*)d_in[3], *wv = (const bf16*)d_in[4], *wo = (const bf16*)d_in[5],
             *wg = (const bf16*)d_in[8], *wu = (const bf16*)d_in[9], *wd = (const bf16*)d_in[10];
  static EncodeFn enc = nullptr;
  static Args a;
  if (!enc) {
    void* fn = nullptr; cudaDriverEntryPointQueryResult qr;
    cudaGetDriverEntryPoint("cuTensorMapEncodeTiled", &fn, cudaEnableDefault, &qr);
    enc = (EncodeFn)fn;
    cudaFuncSetAttribute(fused_kernel, cudaFuncAttributeMaxDynamicSharedMemorySize, K_SMEM);
    build_schedule(a);
  }
  make_map(enc, &a.tmq, wq, HD, DM, 64, 128); make_map(enc, &a.tmk, wk, HD, DM, 64, 128); make_map(enc, &a.tmv, wv, HD, DM, 64, 128);
  make_map(enc, &a.tmo, wo, DM, HD, 64, 128);
  int rc = make_map5(enc, &a.pw[0], wk, HD, DM, 4, true) | make_map5(enc, &a.pw[1], wv, HD, DM, 4, true) | make_map5(enc, &a.pw[2], wq, HD, DM, 4, true) |
           make_map5(enc, &a.pb[0], wg, FF, DM, 2, true) | make_map5(enc, &a.pb[1], wu, FF, DM, 2, true) |
           make_map5(enc, &a.pb[2], wo, DM, HD, 2, true) | make_map5(enc, &a.pb[3], wd, DM, FF, 2, false);
  if (rc) return;
  a.x = (const bf16*)d_in[0]; a.mem0 = (const bf16*)d_in[1]; a.wo = wo; a.gate_w = (const bf16*)d_in[11]; a.out = (bf16*)d_out;
  cudaLaunchConfig_t cfg = {};
  cfg.gridDim = dim3(NCTA); cfg.blockDim = dim3(384); cfg.dynamicSmemBytes = K_SMEM; cfg.stream = cudaStreamPerThread;
  cudaLaunchAttribute at[1];
  at[0].id = cudaLaunchAttributeClusterDimension; at[0].val.clusterDim.x = 2; at[0].val.clusterDim.y = 1; at[0].val.clusterDim.z = 1;
  cfg.attrs = at; cfg.numAttrs = 1;
  cudaLaunchKernelEx(&cfg, fused_kernel, a);
}
```

```cpp
#include <cuda_runtime.h>
#include <cuda_bf16.h>
#include <cuda_fp16.h>
#include <cuda.h>
#include <stdint.h>

typedef __nv_bfloat16 bf16;
#define FAT_REGS "216"
#define AUX_REGS "72"
#define WO_QK 6
#define WO_AT 5
#define WO_EARLY 16
#define WO_PAR 2
#define WV_A 10
#define FLAG_O red_relaxed
#define GLU_EARLY 11
#define LAG_K 2
#define LAG_U 1
#define PF_A 6
#define PF_X 3
#define DISCARD 1
#define PING 2
#define PF_WO 0
#define V_FIRST 1
#define PERM 4
#define NAP 64
#define P6 8
#define SKIP_LAST 0
#define FS 128
#define EARLY_W 0
#define EARLY_FLAG 1
#define POLL_DELAY 5

constexpr int SEQ = 2048, DM = 512, NH = 32, DH = 128, SEGL = 32, NSEG = 64, FF = 1792;
constexpr int HD = NH * DH;
constexpr int KA = HD + FF;
constexpr int NCTA = 132, NGC = 34, MAXJOBS = 320;
constexpr int BLK_BYTES = 24576;
constexpr int RING_SLOT = 32768;
constexpr int A_TILE = KA / 32 * 1024;
constexpr int SPIN_LIMIT = 1 << 20;

__device__ __align__(1024) uint8_t g_qkv[(size_t)NSEG * NH * BLK_BYTES];
__device__ __align__(1024) uint8_t g_a[(size_t)SEQ * KA * 2];
__device__ __align__(1024) float g_acc[(size_t)SEQ * DM];
__device__ unsigned g_fq[NSEG * NH];
__device__ unsigned g_fh[128 * FS];
__device__ unsigned g_fo[128 * FS];
__device__ unsigned g_fc[256 * FS];
__device__ __align__(1024) uint8_t g_ring[16 * RING_SLOT];
__device__ __align__(128) unsigned g_gate[SEQ];
__device__ uint4 g_pub[64];
__device__ unsigned g_done;
__device__ int g_err;

__device__ __forceinline__ uint32_t smem_u32(const void* p) { return (uint32_t)__cvta_generic_to_shared(p); }
__device__ __forceinline__ uint32_t mapa(uint32_t a, uint32_t rank) { uint32_t r; asm volatile("mapa.shared::cluster.u32 %0, %1, %2;" : "=r"(r) : "r"(a), "r"(rank)); return r; }
__device__ __forceinline__ void mbar_init(uint32_t a, uint32_t cnt) { asm volatile("mbarrier.init.shared::cta.b64 [%0], %1;" :: "r"(a), "r"(cnt) : "memory"); }
__device__ __forceinline__ void mbar_expect_tx(uint32_t a, uint32_t bytes) { asm volatile("mbarrier.arrive.expect_tx.shared::cta.b64 _, [%0], %1;" :: "r"(a), "r"(bytes) : "memory"); }
__device__ __forceinline__ bool mbar_try(uint32_t a, uint32_t parity) {
  uint32_t ok;
  asm volatile("{ .reg .pred p; mbarrier.try_wait.parity.shared::cta.b64 p, [%1], %2; selp.u32 %0, 1, 0, p; }" : "=r"(ok) : "r"(a), "r"(parity) : "memory");
  return ok;
}
__device__ __forceinline__ bool mbar_try_cluster(uint32_t a, uint32_t parity) {
  uint32_t ok;
  asm volatile("{ .reg .pred p; mbarrier.try_wait.parity.acquire.cluster.shared::cta.b64 p, [%1], %2; selp.u32 %0, 1, 0, p; }" : "=r"(ok) : "r"(a), "r"(parity) : "memory");
  return ok;
}
__device__ __forceinline__ bool give_up(int it, int code) {
  if ((it & 1023) != 0) return false;
  if (it < SPIN_LIMIT && *reinterpret_cast<volatile int*>(&g_err) == 0) return false;
  if (it >= SPIN_LIMIT) g_err = code;
  return true;
}
__device__ __forceinline__ void mbar_wait(uint32_t a, uint32_t parity) {
  int it = 0;
  while (!mbar_try(a, parity)) { if (give_up(++it, 1)) break; }
}
__device__ __forceinline__ void mbar_wait1(uint32_t a, uint32_t parity) {
  asm volatile("{ .reg .pred p; .reg .u32 c; mov.u32 c, 0;\nW: mbarrier.try_wait.parity.shared::cta.b64 p, [%0], %1;\n"
               "add.u32 c, c, 1; setp.lt.and.u32 p, c, 65536, !p; @p bra W; }" :: "r"(a), "r"(parity) : "memory");
}
__device__ __forceinline__ void mbar_wait_cluster(uint32_t a, uint32_t parity) {
  int it = 0;
  while (!mbar_try_cluster(a, parity)) { if (give_up(++it, 2)) break; }
}
template <int ID, int N> __device__ __forceinline__ void bar_sync() { asm volatile("bar.sync %0, %1;" :: "n"(ID), "n"(N) : "memory"); }
template <int ID, int N> __device__ __forceinline__ void bar_arrive() { asm volatile("bar.arrive %0, %1;" :: "n"(ID), "n"(N) : "memory"); }
__device__ __forceinline__ void bar_sync_id(int id, int n) { asm volatile("bar.sync %0, %1;" :: "r"(id), "r"(n) : "memory"); }
__device__ __forceinline__ void tma2d(uint32_t dst, const CUtensorMap* tm, int c0, int c1, uint32_t mb) {
  asm volatile("cp.async.bulk.tensor.2d.shared::cluster.global.mbarrier::complete_tx::bytes [%0], [%1, {%3, %4}], [%2];"
               :: "r"(dst), "l"((uint64_t)tm), "r"(mb), "r"(c0), "r"(c1) : "memory");
}
__device__ __forceinline__ void bulk_g2s(uint32_t dst, const void* src, uint32_t bytes, uint32_t mb) {
  asm volatile("cp.async.bulk.shared::cluster.global.mbarrier::complete_tx::bytes [%0], [%1], %2, [%3];"
               :: "r"(dst), "l"(src), "r"(bytes), "r"(mb) : "memory");
}
__device__ __forceinline__ void ldm4(uint32_t* r, uint32_t a) {
  asm volatile("ldmatrix.sync.aligned.m8n8.x4.shared.b16 {%0,%1,%2,%3}, [%4];" : "=r"(r[0]), "=r"(r[1]), "=r"(r[2]), "=r"(r[3]) : "r"(a) : "memory");
}
__device__ __forceinline__ void ldm4t(uint32_t* r, uint32_t a) {
  asm volatile("ldmatrix.sync.aligned.m8n8.x4.trans.shared.b16 {%0,%1,%2,%3}, [%4];" : "=r"(r[0]), "=r"(r[1]), "=r"(r[2]), "=r"(r[3]) : "r"(a) : "memory");
}
__device__ __forceinline__ void stm4(uint32_t a, uint32_t r0, uint32_t r1, uint32_t r2, uint32_t r3) {
  asm volatile("stmatrix.sync.aligned.m8n8.x4.shared.b16 [%0], {%1,%2,%3,%4};" :: "r"(a), "r"(r0), "r"(r1), "r"(r2), "r"(r3) : "memory");
}
__device__ __forceinline__ void stm4t(uint32_t a, uint32_t r0, uint32_t r1, uint32_t r2, uint32_t r3) {
  asm volatile("stmatrix.sync.aligned.m8n8.x4.trans.shared.b16 [%0], {%1,%2,%3,%4};" :: "r"(a), "r"(r0), "r"(r1), "r"(r2), "r"(r3) : "memory");
}
__device__ __forceinline__ void hma16(float* d, const uint32_t* a, uint32_t b0, uint32_t b1) {
  asm volatile("mma.sync.aligned.m16n8k16.row.col.f32.f16.f16.f32 {%0,%1,%2,%3}, {%4,%5,%6,%7}, {%8,%9}, {%0,%1,%2,%3};"
               : "+f"(d[0]), "+f"(d[1]), "+f"(d[2]), "+f"(d[3]) : "r"(a[0]), "r"(a[1]), "r"(a[2]), "r"(a[3]), "r"(b0), "r"(b1));
}
__device__ __forceinline__ void hma16z(float* d, const uint32_t* a, uint32_t b0, uint32_t b1) {
  asm volatile("mma.sync.aligned.m16n8k16.row.col.f32.f16.f16.f32 {%0,%1,%2,%3}, {%4,%5,%6,%7}, {%8,%9}, {%10,%10,%10,%10};"
               : "=f"(d[0]), "=f"(d[1]), "=f"(d[2]), "=f"(d[3]) : "r"(a[0]), "r"(a[1]), "r"(a[2]), "r"(a[3]), "r"(b0), "r"(b1), "f"(0.f));
}
__device__ __forceinline__ void mma16(float* d, uint32_t a0, uint32_t a1, uint32_t a2, uint32_t a3, uint32_t b0, uint32_t b1) {
  asm volatile("mma.sync.aligned.m16n8k16.row.col.f32.bf16.bf16.f32 {%0,%1,%2,%3}, {%4,%5,%6,%7}, {%8,%9}, {%0,%1,%2,%3};"
               : "+f"(d[0]), "+f"(d[1]), "+f"(d[2]), "+f"(d[3]) : "r"(a0), "r"(a1), "r"(a2), "r"(a3), "r"(b0), "r"(b1));
}
__device__ __forceinline__ void mma16z(float* d, uint32_t a0, uint32_t a1, uint32_t a2, uint32_t a3, uint32_t b0, uint32_t b1) {
  asm volatile("mma.sync.aligned.m16n8k16.row.col.f32.bf16.bf16.f32 {%0,%1,%2,%3}, {%4,%5,%6,%7}, {%8,%9}, {%10,%10,%10,%10};"
               : "=f"(d[0]), "=f"(d[1]), "=f"(d[2]), "=f"(d[3]) : "r"(a0), "r"(a1), "r"(a2), "r"(a3), "r"(b0), "r"(b1), "f"(0.f));
}
__device__ __forceinline__ void mma8(float* d, uint32_t a0, uint32_t a1, uint32_t b0) {
  asm volatile("mma.sync.aligned.m16n8k8.row.col.f32.bf16.bf16.f32 {%0,%1,%2,%3}, {%4,%5}, {%6}, {%0,%1,%2,%3};"
               : "+f"(d[0]), "+f"(d[1]), "+f"(d[2]), "+f"(d[3]) : "r"(a0), "r"(a1), "r"(b0));
}
__device__ __forceinline__ void mma8z(float* d, uint32_t a0, uint32_t a1, uint32_t b0) {
  asm volatile("mma.sync.aligned.m16n8k8.row.col.f32.bf16.bf16.f32 {%0,%1,%2,%3}, {%4,%5}, {%6}, {%7,%7,%7,%7};"
               : "=f"(d[0]), "=f"(d[1]), "=f"(d[2]), "=f"(d[3]) : "r"(a0), "r"(a1), "r"(b0), "f"(0.f));
}
__device__ __forceinline__ uint32_t pack_bf16(float lo, float hi) { uint32_t r; asm("cvt.rn.bf16x2.f32 %0, %1, %2;" : "=r"(r) : "f"(hi), "f"(lo)); return r; }
__device__ __forceinline__ uint32_t pack_f16(float lo, float hi) { uint32_t r; asm("cvt.rn.f16x2.f32 %0, %1, %2;" : "=r"(r) : "f"(hi), "f"(lo)); return r; }
__device__ __forceinline__ float2 unpack_f16(uint32_t v) { return __half22float2(*reinterpret_cast<__half2*>(&v)); }
__device__ __forceinline__ uint32_t absmax2(uint32_t a, uint32_t b) { uint32_t r; asm("max.xorsign.abs.bf16x2 %0, %1, %2;" : "=r"(r) : "r"(a), "r"(b)); return r; }
__device__ __forceinline__ uint32_t absmax2h(uint32_t a, uint32_t b) { uint32_t r; asm("max.xorsign.abs.f16x2 %0, %1, %2;" : "=r"(r) : "r"(a), "r"(b)); return r; }
__device__ __forceinline__ uint32_t hadd2(uint32_t a, uint32_t b) { uint32_t r; asm("add.rn.bf16x2 %0, %1, %2;" : "=r"(r) : "r"(a), "r"(b)); return r; }
__device__ __forceinline__ void sts64(uint32_t a, uint32_t x, uint32_t y) { asm volatile("st.shared.v2.u32 [%0], {%1,%2};" :: "r"(a), "r"(x), "r"(y) : "memory"); }
__device__ __forceinline__ uint2 lds64(uint32_t a) { uint2 v; asm volatile("ld.shared.v2.u32 {%0,%1}, [%2];" : "=r"(v.x), "=r"(v.y) : "r"(a) : "memory"); return v; }
__device__ __forceinline__ void lds64r(uint32_t* r, uint32_t a) { asm volatile("ld.shared.v2.u32 {%0,%1}, [%2];" : "=r"(r[0]), "=r"(r[1]) : "r"(a) : "memory"); }
__device__ __forceinline__ void ldv_s(uint32_t* r, uint32_t a) {
  asm volatile("ld.volatile.shared.v4.u32 {%0,%1,%2,%3}, [%4];" : "=r"(r[0]), "=r"(r[1]), "=r"(r[2]), "=r"(r[3]) : "r"(a) : "memory");
}
__device__ __forceinline__ float ex2v(float x) { float r; asm volatile("ex2.approx.ftz.f32 %0, %1;" : "=f"(r) : "f"(x)); return r; }
__device__ __forceinline__ uint32_t fold_absmax(uint32_t m) { m &= 0x7FFF7FFFu; return max(m & 0xFFFFu, m >> 16); }
__device__ __forceinline__ float ex2(float x) { float r; asm("ex2.approx.ftz.f32 %0, %1;" : "=f"(r) : "f"(x)); return r; }
__device__ __forceinline__ void sts32(uint32_t a, uint32_t v) { asm volatile("st.shared.u32 [%0], %1;" :: "r"(a), "r"(v) : "memory"); }
__device__ __forceinline__ void sts64f(uint32_t a, float x, float y) { asm volatile("st.shared.v2.f32 [%0], {%1,%2};" :: "r"(a), "f"(x), "f"(y) : "memory"); }
__device__ __forceinline__ float2 lds64f(uint32_t a) { float2 v; asm volatile("ld.shared.v2.f32 {%0,%1}, [%2];" : "=f"(v.x), "=f"(v.y) : "r"(a) : "memory"); return v; }
__device__ __forceinline__ uint32_t lds32(uint32_t a) { uint32_t v; asm volatile("ld.shared.u32 %0, [%1];" : "=r"(v) : "r"(a) : "memory"); return v; }
__device__ __forceinline__ uint4 lds128(uint32_t a) { uint4 v; asm volatile("ld.shared.v4.u32 {%0,%1,%2,%3}, [%4];" : "=r"(v.x), "=r"(v.y), "=r"(v.z), "=r"(v.w) : "r"(a) : "memory"); return v; }
__device__ __forceinline__ void st_async32(uint32_t a, uint32_t v, uint32_t mb) {
  asm volatile("st.async.weak.shared::cluster.mbarrier::complete_tx::bytes.b32 [%0], %1, [%2];" :: "r"(a), "r"(v), "r"(mb) : "memory");
}
__device__ __forceinline__ void st_async64(uint32_t a, uint32_t x, uint32_t y, uint32_t mb) {
  asm volatile("st.async.weak.shared::cluster.mbarrier::complete_tx::bytes.v2.b32 [%0], {%1,%2}, [%3];" :: "r"(a), "r"(x), "r"(y), "r"(mb) : "memory");
}
__device__ __forceinline__ void st_async128(uint32_t a, uint32_t x, uint32_t y, uint32_t z, uint32_t w, uint32_t mb) {
  asm volatile("st.async.weak.shared::cluster.mbarrier::complete_tx::bytes.v4.b32 [%0], {%1,%2,%3,%4}, [%5];" :: "r"(a), "r"(x), "r"(y), "r"(z), "r"(w), "r"(mb) : "memory");
}
__device__ __forceinline__ void sts128(uint32_t a, uint32_t x, uint32_t y, uint32_t z, uint32_t w) {
  asm volatile("st.shared.v4.u32 [%0], {%1,%2,%3,%4};" :: "r"(a), "r"(x), "r"(y), "r"(z), "r"(w) : "memory");
}
__device__ __forceinline__ void lds128r(uint32_t* r, uint32_t a) {
  asm volatile("ld.shared.v4.u32 {%0,%1,%2,%3}, [%4];" : "=r"(r[0]), "=r"(r[1]), "=r"(r[2]), "=r"(r[3]) : "r"(a) : "memory");
}
__device__ __forceinline__ float4 lds128f(uint32_t a) { float4 v; asm volatile("ld.shared.v4.f32 {%0,%1,%2,%3}, [%4];" : "=f"(v.x), "=f"(v.y), "=f"(v.z), "=f"(v.w) : "r"(a) : "memory"); return v; }
__device__ __forceinline__ void mbar_arrive(uint32_t a) { asm volatile("mbarrier.arrive.shared::cta.b64 _, [%0];" :: "r"(a) : "memory"); }
__device__ __forceinline__ uint32_t movm(uint32_t a) { uint32_t d; asm volatile("movmatrix.sync.aligned.m8n8.trans.b16 %0, %1;" : "=r"(d) : "r"(a)); return d; }
__device__ __forceinline__ float rcp(float x) { float r; asm("rcp.approx.ftz.f32 %0, %1;" : "=f"(r) : "f"(x)); return r; }
__device__ __forceinline__ uint32_t f16_to_bf16(uint32_t v) { const float2 f = unpack_f16(v); return pack_bf16(f.x, f.y); }
__device__ __forceinline__ uint4 ldv128(const void* p) {
  uint4 v; asm volatile("ld.volatile.global.v4.u32 {%0,%1,%2,%3}, [%4];" : "=r"(v.x), "=r"(v.y), "=r"(v.z), "=r"(v.w) : "l"(p) : "memory"); return v;
}
__device__ __forceinline__ uint32_t ldv32(const void* p) { uint32_t v; asm volatile("ld.volatile.global.u32 %0, [%1];" : "=r"(v) : "l"(p) : "memory"); return v; }
__device__ __forceinline__ float bf_lo(uint32_t v) { return __uint_as_float(v << 16); }
__device__ __forceinline__ float bf_hi(uint32_t v) { return __uint_as_float(v & 0xFFFF0000u); }

__device__ __forceinline__ void wgmma_rs192(float* d, uint32_t a0, uint32_t a1, uint32_t a2, uint32_t a3, uint64_t desc, int acc) {
  asm volatile("{ .reg .pred p; setp.ne.b32 p, %101, 0;\n"
    "wgmma.mma_async.sync.aligned.m64n192k16.f32.bf16.bf16 {%0,%1,%2,%3,%4,%5,%6,%7,%8,%9,%10,%11,%12,%13,%14,%15,%16,%17,%18,%19,%20,%21,%22,%23,%24,%25,%26,%27,%28,%29,%30,%31,%32,%33,%34,%35,%36,%37,%38,%39,%40,%41,%42,%43,%44,%45,%46,%47,%48,%49,%50,%51,%52,%53,%54,%55,%56,%57,%58,%59,%60,%61,%62,%63,%64,%65,%66,%67,%68,%69,%70,%71,%72,%73,%74,%75,%76,%77,%78,%79,%80,%81,%82,%83,%84,%85,%86,%87,%88,%89,%90,%91,%92,%93,%94,%95}, {%96,%97,%98,%99}, %100, p, 1, 1, 1; }"
    :
      "+f"(d[0]), "+f"(d[1]), "+f"(d[2]), "+f"(d[3]), "+f"(d[4]), "+f"(d[5]), "+f"(d[6]), "+f"(d[7]), "+f"(d[8]), "+f"(d[9]), "+f"(d[10]), "+f"(d[11]),
      "+f"(d[12]), "+f"(d[13]), "+f"(d[14]), "+f"(d[15]), "+f"(d[16]), "+f"(d[17]), "+f"(d[18]), "+f"(d[19]), "+f"(d[20]), "+f"(d[21]), "+f"(d[22]), "+f"(d[23]),
      "+f"(d[24]), "+f"(d[25]), "+f"(d[26]), "+f"(d[27]), "+f"(d[28]), "+f"(d[29]), "+f"(d[30]), "+f"(d[31]), "+f"(d[32]), "+f"(d[33]), "+f"(d[34]), "+f"(d[35]),
      "+f"(d[36]), "+f"(d[37]), "+f"(d[38]), "+f"(d[39]), "+f"(d[40]), "+f"(d[41]), "+f"(d[42]), "+f"(d[43]), "+f"(d[44]), "+f"(d[45]), "+f"(d[46]), "+f"(d[47]),
      "+f"(d[48]), "+f"(d[49]), "+f"(d[50]), "+f"(d[51]), "+f"(d[52]), "+f"(d[53]), "+f"(d[54]), "+f"(d[55]), "+f"(d[56]), "+f"(d[57]), "+f"(d[58]), "+f"(d[59]),
      "+f"(d[60]), "+f"(d[61]), "+f"(d[62]), "+f"(d[63]), "+f"(d[64]), "+f"(d[65]), "+f"(d[66]), "+f"(d[67]), "+f"(d[68]), "+f"(d[69]), "+f"(d[70]), "+f"(d[71]),
      "+f"(d[72]), "+f"(d[73]), "+f"(d[74]), "+f"(d[75]), "+f"(d[76]), "+f"(d[77]), "+f"(d[78]), "+f"(d[79]), "+f"(d[80]), "+f"(d[81]), "+f"(d[82]), "+f"(d[83]),
      "+f"(d[84]), "+f"(d[85]), "+f"(d[86]), "+f"(d[87]), "+f"(d[88]), "+f"(d[89]), "+f"(d[90]), "+f"(d[91]), "+f"(d[92]), "+f"(d[93]), "+f"(d[94]), "+f"(d[95])
    : "r"(a0), "r"(a1), "r"(a2), "r"(a3), "l"(desc), "r"(acc));
}

__device__ __forceinline__ void wgmma_rs256(float* d, uint32_t a0, uint32_t a1, uint32_t a2, uint32_t a3, uint64_t desc, int acc) {
  asm volatile("{ .reg .pred p; setp.ne.b32 p, %133, 0;\n"
    "wgmma.mma_async.sync.aligned.m64n256k16.f32.bf16.bf16 {%0,%1,%2,%3,%4,%5,%6,%7,%8,%9,%10,%11,%12,%13,%14,%15,%16,%17,%18,%19,%20,%21,%22,%23,%24,%25,%26,%27,%28,%29,%30,%31,%32,%33,%34,%35,%36,%37,%38,%39,%40,%41,%42,%43,%44,%45,%46,%47,%48,%49,%50,%51,%52,%53,%54,%55,%56,%57,%58,%59,%60,%61,%62,%63,%64,%65,%66,%67,%68,%69,%70,%71,%72,%73,%74,%75,%76,%77,%78,%79,%80,%81,%82,%83,%84,%85,%86,%87,%88,%89,%90,%91,%92,%93,%94,%95,%96,%97,%98,%99,%100,%101,%102,%103,%104,%105,%106,%107,%108,%109,%110,%111,%112,%113,%114,%115,%116,%117,%118,%119,%120,%121,%122,%123,%124,%125,%126,%127}, {%128,%129,%130,%131}, %132, p, 1, 1, 1; }"
    :
      "+f"(d[0]), "+f"(d[1]), "+f"(d[2]), "+f"(d[3]), "+f"(d[4]), "+f"(d[5]), "+f"(d[6]), "+f"(d[7]), "+f"(d[8]), "+f"(d[9]), "+f"(d[10]), "+f"(d[11]),
      "+f"(d[12]), "+f"(d[13]), "+f"(d[14]), "+f"(d[15]), "+f"(d[16]), "+f"(d[17]), "+f"(d[18]), "+f"(d[19]), "+f"(d[20]), "+f"(d[21]), "+f"(d[22]), "+f"(d[23]),
      "+f"(d[24]), "+f"(d[25]), "+f"(d[26]), "+f"(d[27]), "+f"(d[28]), "+f"(d[29]), "+f"(d[30]), "+f"(d[31]), "+f"(d[32]), "+f"(d[33]), "+f"(d[34]), "+f"(d[35]),
      "+f"(d[36]), "+f"(d[37]), "+f"(d[38]), "+f"(d[39]), "+f"(d[40]), "+f"(d[41]), "+f"(d[42]), "+f"(d[43]), "+f"(d[44]), "+f"(d[45]), "+f"(d[46]), "+f"(d[47]),
      "+f"(d[48]), "+f"(d[49]), "+f"(d[50]), "+f"(d[51]), "+f"(d[52]), "+f"(d[53]), "+f"(d[54]), "+f"(d[55]), "+f"(d[56]), "+f"(d[57]), "+f"(d[58]), "+f"(d[59]),
      "+f"(d[60]), "+f"(d[61]), "+f"(d[62]), "+f"(d[63]), "+f"(d[64]), "+f"(d[65]), "+f"(d[66]), "+f"(d[67]), "+f"(d[68]), "+f"(d[69]), "+f"(d[70]), "+f"(d[71]),
      "+f"(d[72]), "+f"(d[73]), "+f"(d[74]), "+f"(d[75]), "+f"(d[76]), "+f"(d[77]), "+f"(d[78]), "+f"(d[79]), "+f"(d[80]), "+f"(d[81]), "+f"(d[82]), "+f"(d[83]),
      "+f"(d[84]), "+f"(d[85]), "+f"(d[86]), "+f"(d[87]), "+f"(d[88]), "+f"(d[89]), "+f"(d[90]), "+f"(d[91]), "+f"(d[92]), "+f"(d[93]), "+f"(d[94]), "+f"(d[95]),
      "+f"(d[96]), "+f"(d[97]), "+f"(d[98]), "+f"(d[99]), "+f"(d[100]), "+f"(d[101]), "+f"(d[102]), "+f"(d[103]), "+f"(d[104]), "+f"(d[105]), "+f"(d[106]), "+f"(d[107]),
      "+f"(d[108]), "+f"(d[109]), "+f"(d[110]), "+f"(d[111]), "+f"(d[112]), "+f"(d[113]), "+f"(d[114]), "+f"(d[115]), "+f"(d[116]), "+f"(d[117]), "+f"(d[118]), "+f"(d[119]),
      "+f"(d[120]), "+f"(d[121]), "+f"(d[122]), "+f"(d[123]), "+f"(d[124]), "+f"(d[125]), "+f"(d[126]), "+f"(d[127])
    : "r"(a0), "r"(a1), "r"(a2), "r"(a3), "l"(desc), "r"(acc));
}

__device__ __forceinline__ void wg_fence() { asm volatile("wgmma.fence.sync.aligned;" ::: "memory"); }
__device__ __forceinline__ void wg_commit() { asm volatile("wgmma.commit_group.sync.aligned;" ::: "memory"); }
template <int N> __device__ __forceinline__ void wg_wait() { asm volatile("wgmma.wait_group.sync.aligned %0;" :: "n"(N) : "memory"); }
__device__ __forceinline__ void tma5d(uint32_t dst, const CUtensorMap* tm, int c0, int c4, uint32_t mb) {
  asm volatile("cp.async.bulk.tensor.5d.shared::cluster.global.mbarrier::complete_tx::bytes [%0], [%1, {%3, %5, %5, %5, %4}], [%2];"
               :: "r"(dst), "l"((uint64_t)tm), "r"(mb), "r"(c0), "r"(c4), "r"(0) : "memory");
}
__device__ __forceinline__ void tma5d_mc(uint32_t dst, const CUtensorMap* tm, int c0, int c4, uint32_t mb) {
  asm volatile("cp.async.bulk.tensor.5d.shared::cluster.global.mbarrier::complete_tx::bytes.multicast::cluster [%0], [%1, {%3, %5, %5, %5, %4}], [%2], %6;"
               :: "r"(dst), "l"((uint64_t)tm), "r"(mb), "r"(c0), "r"(c4), "r"(0), "h"((unsigned short)3) : "memory");
}
__device__ __forceinline__ void mbar_arrive_cluster(uint32_t a) { asm volatile("mbarrier.arrive.shared::cluster.b64 _, [%0];" :: "r"(a) : "memory"); }
__device__ __forceinline__ void ldg128(uint32_t* r, const uint8_t* p) {
  asm volatile("ld.global.L1::no_allocate.v4.u32 {%0,%1,%2,%3}, [%4];" : "=r"(r[0]), "=r"(r[1]), "=r"(r[2]), "=r"(r[3]) : "l"(p) : "memory");
}
__device__ __forceinline__ uint32_t ld_relaxed(const unsigned* p) { uint32_t v; asm volatile("ld.relaxed.gpu.global.u32 %0, [%1];" : "=r"(v) : "l"(p) : "memory"); return v; }
__device__ __forceinline__ void st_relaxed(unsigned* p, uint32_t v) { asm volatile("st.relaxed.gpu.global.u32 [%0], %1;" :: "l"(p), "r"(v) : "memory"); }
__device__ __forceinline__ uint32_t ld_acquire(const unsigned* p) { uint32_t v; asm volatile("ld.acquire.gpu.global.u32 %0, [%1];" : "=r"(v) : "l"(p) : "memory"); return v; }
__device__ __forceinline__ void red_release(unsigned* p) { asm volatile("red.release.gpu.global.add.u32 [%0], 1;" :: "l"(p) : "memory"); }
__device__ __forceinline__ void red_relaxed(unsigned* p) { asm volatile("red.relaxed.gpu.global.add.u32 [%0], 1;" :: "l"(p) : "memory"); }
__device__ __forceinline__ void red4(float4* p, const float* v) {
  asm volatile("red.relaxed.gpu.global.add.v4.f32 [%0], {%1,%2,%3,%4};" :: "l"(p), "f"(v[0]), "f"(v[1]), "f"(v[2]), "f"(v[3]) : "memory");
}
__device__ __forceinline__ void fence_gpu() { asm volatile("fence.acq_rel.gpu;" ::: "memory"); }
__device__ __forceinline__ void wait_count(const unsigned* p, uint32_t target) {
  int it = 0;
  while (__any_sync(~0u, (int)(ld_acquire(p) - target) < 0)) { if (give_up(++it, 5)) break; __nanosleep(NAP); }
}

__device__ __forceinline__ void check_gate(uint32_t& g0, uint32_t& g1, const unsigned* p, uint32_t tag) {
  int it = 0;
  while (__builtin_expect(__any_sync(~0u, (((g0 ^ tag) | (g1 ^ tag)) & 15) != 0), 0)) {
    if (give_up(++it, 6)) break;
    g0 = ld_relaxed(p); g1 = ld_relaxed(p + 8);
  }
}

constexpr int G_ST = 32768, G_NST = 7, G_MB = G_ST * G_NST, GB_W = G_MB  , GB_FULL = G_MB + 32, GB_EMPTY = G_MB + 96, GB_EV = G_MB + 160, G_NEV = 48,
              G_SMEM = GB_EV + 16 * G_NEV;

constexpr int C_SW = 0, C_WO = 65536, C_KVQ = 131072, KVQ_ST = 20480, C_QM = 192512, C_MEM = 196608,
              C_VM = 204800  , C_KX = 212992, C_OT = 215040, C_SL = 217088, C_SR = 219136, C_MX = 220160, C_MISC = 221184;
constexpr int MB_WQ = C_MISC, MB_WK = C_MISC + 8, MB_WV = C_MISC + 16, MB_WO = C_MISC + 24, MB_K = C_MISC + 48,
              MB_S = C_MISC + 64, MB_V = C_MISC + 72, MB_KVQ = C_MISC + 80  ;
constexpr int TX_S = 1024, TX_V = 2048;
constexpr int C_WE = C_MISC + 112;
constexpr int C_UP = C_MISC + 128;
constexpr int C_WM = C_MISC + 512;
constexpr int C_XE = C_MISC + 256;
constexpr int C_SU = C_MISC + 704;
constexpr int C_SX = C_MISC + 768;
constexpr int C_DBG = C_SX + 4096;
constexpr int C_SMEM = C_DBG;

__device__ __forceinline__ const uint8_t* gptr(uint32_t lo, uint32_t hi) { uint64_t r; asm("mov.b64 %0, {%1, %2};" : "=l"(r) : "r"(lo), "r"(hi)); return reinterpret_cast<const uint8_t*>(r); }
__device__ __forceinline__ uint32_t prmt(uint32_t a, uint32_t b, uint32_t s) { uint32_t r; asm("prmt.b32 %0, %1, %2, %3;" : "=r"(r) : "r"(a), "r"(b), "r"(s)); return r; }
#define FENCE_BB asm volatile("{ .reg .pred p; setp.ne.u32 p, %0, 0; @p exit; }" :: "r"(args.zero) : "memory")
__device__ __forceinline__ int fresh(int v) { asm volatile("" : "+r"(v)); return v; }

struct Args {
  CUtensorMap tmq, tmk, tmv, tmo;
  CUtensorMap pw[3];
  CUtensorMap pb[4];
  const bf16* x; const bf16* mem0; const bf16* wo; const bf16* gate_w; bf16* out;
  uint32_t zero;
  uint16_t first[NGC + 2];
  uint32_t job[MAXJOBS];
};
constexpr uint32_t M_CONT = 0, M_STORE = 1, M_RED = 2, M_OUT = 3;
constexpr int K_TAG = C_SMEM > G_SMEM ? C_SMEM : G_SMEM, K_SMEM = K_TAG + 32;

__device__ __forceinline__ void load_a(uint32_t* a, const uint8_t* p0, const uint8_t* p1, int d = 64) {
  ldg128(a, p0); ldg128(a + 4, p1); ldg128(a + 8, p0 + d); ldg128(a + 12, p1 + d);
}
__device__ __forceinline__ void frag_a(uint32_t* u, const uint32_t* a, uint32_t z) {
#pragma unroll
  for (int i = 0; i < 16; i++) { u[i] = a[(i & 8) | ((i & 1) << 2) | (i & 2) | ((i >> 2) & 1)] ^ z; asm volatile("" : "+r"(u[i])); }
}
#define GSTAMP(i)
#define QSTAMP(it, k)
#define PSTAMP(t, i)

__global__ void __launch_bounds__(384, 1)
fused_kernel(const __grid_constant__ Args args) {
  extern __shared__ __align__(1024) uint8_t smem[];
  const int tid = threadIdx.x;
  const int lane = __shfl_sync(~0u, tid & 31, tid & 31);
  const int warp = __shfl_sync(~0u, tid >> 5, 0);
  const int bx = blockIdx.x;
  const int cta = PERM == 0 || bx >= 128 ? bx : ((bx >> PERM) & 1) * 64 + ((bx >> (PERM + 1)) << PERM) + (bx & ((1 << PERM) - 1));
  const int h = (cta >> 1) & 31, j = cta & 1;
  const uint32_t sb = smem_u32(smem);
  if (warp == (cta < 64 ? 2 : 11) && lane < 11 && (lane < 4) == (cta < 64)) asm volatile("prefetch.tensormap [%0];" :: "l"(&args.tmq + lane) : "memory");
  if (tid == (cta < 64 ? 32 : 320)) sts32(sb + K_TAG, ldv32(&g_done) / NCTA + 1);

  if (cta >= 64 && tid >= 288 && tid < 288 + 2 * G_NEV) mbar_init(sb + GB_EV + 8 * (tid - 288), 4);
  if (tid == 256 && cta >= 64) {
    for (int i = 0; i < G_NST; i++) { mbar_init(sb + GB_FULL + 8 * i, 1); mbar_init(sb + GB_EMPTY + 8 * i, 16); }
    asm volatile("fence.mbarrier_init.release.cluster;" ::: "memory");
  }
  if (tid == 0 && cta < 64) {
    mbar_init(sb + MB_WQ, 1); mbar_init(sb + MB_WK, 1); mbar_init(sb + MB_WV, 1); mbar_init(sb + MB_WO, 1);
    mbar_init(sb + MB_K, 1); mbar_init(sb + MB_S, 1); mbar_init(sb + MB_V, 9);
    for (int i = 0; i < 3; i++) mbar_init(sb + MB_KVQ + 8 * i, 1);
    asm volatile("fence.mbarrier_init.release.cluster;" ::: "memory");
    mbar_expect_tx(sb + MB_K, 1024); mbar_expect_tx(sb + MB_S, TX_S); mbar_expect_tx(sb + MB_V, TX_V);
  }
  PSTAMP(0, 0);
  auto start = [&]() {
    asm volatile("barrier.cluster.arrive.relaxed.aligned; bar.sync 0; barrier.cluster.wait.aligned;" ::: "memory");
    return lds32(sb + K_TAG);
  };
  uint8_t* const ring = reinterpret_cast<uint8_t*>((reinterpret_cast<uintptr_t>(g_ring) + 8 * RING_SLOT - 1) & ~(uintptr_t)(8 * RING_SLOT - 1));
  auto issue_stage = [&](int seg, int stg) {
    const uint32_t mb = sb + MB_KVQ + 8 * stg;
    mbar_expect_tx(mb, KVQ_ST);
    bulk_g2s(sb + C_KVQ + stg * KVQ_ST, g_qkv + (size_t)(seg * NH + h) * BLK_BYTES + j * 4096, KVQ_ST, mb);
  };

  if (cta >= 64 && warp < 8) {
    const int wg = warp >> 2, w = warp & 3, g = lane >> 2, t = lane & 3;
    const uint64_t dsc_hi = (uint64_t)((2048 >> 4) | (1u << 30)) << 32;
    uint32_t A[4][16], U[2][16];
    {
      const uint8_t* p0 = reinterpret_cast<const uint8_t*>(args.x) + (size_t)(wg * 64 + w * 16 + g) * (DM * 2) + t * 16;
      if (wg == 0 && cta < 128) {
#pragma unroll
        for (int i = 0; i < 4; i++) load_a(A[i], p0 + i * 128, p0 + i * 128 + 8192);
#pragma unroll
        for (int i = 0; i < 16; i++)
          asm volatile("cp.async.cg.shared.global [%0], [%1], 16;" :: "r"(sb + 196608 + i * 2048 + tid * 16), "l"(p0 + 512 + (i >> 1) * 64 + (i & 1) * 8192) : "memory");
        asm volatile("cp.async.wait_all;" ::: "memory");
      }
    }
    const uint32_t tag = start();
    if (wg == 1) {
      const uint8_t* p0 = reinterpret_cast<const uint8_t*>(args.x) + (size_t)(wg * 64 + w * 16 + g) * (DM * 2) + t * 16;
#pragma unroll
      for (int i = 0; i < 4; i++) load_a(A[i], p0 + i * 128, p0 + i * 128 + 8192);
    }
    asm volatile("setmaxnreg.inc.sync.aligned.u32 232;");
    uint32_t ev = sb + GB_EV + wg * (8 * G_NEV);
    auto publish = [&]() { __syncwarp(); if (lane == 0) mbar_arrive(ev); ev += 8; };
    GSTAMP(0);
    if (cta < 128) {
      float acc[96];
      const uint8_t* p0 = reinterpret_cast<const uint8_t*>(args.x) + (size_t)(wg * 64 + w * 16 + g) * (DM * 2) + t * 16;
      const uint64_t dsc = dsc_hi | (uint64_t)(((sb >> 4) & 0x3FFF) | ((65536 >> 4) << 16));
      uint8_t* dst = g_qkv + (size_t)((2 * wg + (w >> 1)) * NH + h) * BLK_BYTES + 4096 + (w & 1) * 4096 + j * 1024 + lane * 16;
      const int dv = 8192 - (w & 1) * 3584 + j * 3072, dq = (w & 1) * 16384 - 4096 + j * 1024;
      for (int it = 0; it < 16; it++) {
        if (wg == 1) bar_sync<1, 256>(); else if (it > 0) bar_sync<2, 256>();
        QSTAMP(it, 0);
#pragma unroll
        for (int kc = 0; kc < 8; kc++) {
          if (it == 0) mbar_wait(sb + GB_W + 8 * (kc >> 1), 0);
          uint32_t* a = U[kc & 1];
          frag_a(a, A[kc & 3], args.zero);
          wg_fence();
          wgmma_rs192(acc, a[0], a[1], a[2], a[3], dsc + kc * 512, kc != 0);
          wgmma_rs192(acc, a[4], a[5], a[6], a[7], dsc + kc * 512 + 64, 1);
          wgmma_rs192(acc, a[8], a[9], a[10], a[11], dsc + kc * 512 + 256, 1);
          wgmma_rs192(acc, a[12], a[13], a[14], a[15], dsc + kc * 512 + 320, 1);
          wg_commit();
          const uint8_t* pn = p0 + (kc < 4 ? (kc + 4) * 128 : 128 * DM * 2 + (kc - 4) * 128);
          if (it == 0 && wg == 0) {
#pragma unroll
            for (int i = 0; i < 4; i++) if (kc < 4) lds128r(A[kc] + 4 * i, sb + 196608 + (kc * 4 + i) * 2048 + tid * 16);
          } else if (kc < 4 || it < 15) load_a(A[kc & 3], pn, pn + 8192);
          if (kc == 0) { QSTAMP(it, 1); }
          if (kc == 4) { QSTAMP(it, 4); }
          if (kc == (it == 0 && wg == 0 ? 6 : PING)) { if (wg == 0) bar_arrive<1, 256>(); else if (it < 15) bar_arrive<2, 256>(); }
          wg_wait<1>();
        }
        wg_wait<0>();
        QSTAMP(it, 2);
#pragma unroll
        for (int b = 0; b < 2; b++) {
          const float* d = acc + 16 * b;
          *reinterpret_cast<uint4*>(dst + b * 512) = make_uint4(pack_bf16(d[0], d[1]), pack_bf16(d[4], d[5]), pack_bf16(d[8], d[9]), pack_bf16(d[12], d[13]));
          *reinterpret_cast<uint4*>(dst + b * 512 + 2048) = make_uint4(pack_bf16(d[2], d[3]), pack_bf16(d[6], d[7]), pack_bf16(d[10], d[11]), pack_bf16(d[14], d[15]));
        }
#pragma unroll
        for (int b = 0; b < 4; b++) {
          const float* d = acc + 32 + 8 * b;
          *reinterpret_cast<uint4*>(dst + dv + b * 1024) = make_uint4(movm(pack_bf16(d[0], d[1])), movm(pack_bf16(d[4], d[5])), movm(pack_bf16(d[2], d[3])), movm(pack_bf16(d[6], d[7])));
          *reinterpret_cast<uint4*>(dst + dq + b * 512) = make_uint4(pack_bf16(d[32], d[33]), pack_bf16(d[34], d[35]), pack_bf16(d[36], d[37]), pack_bf16(d[38], d[39]));
        }
        publish();
        QSTAMP(it, 3);
        p0 += 128 * DM * 2; dst += (size_t)4 * NH * BLK_BYTES;
        if (it == 0 && wg == 0) {
#pragma unroll
          for (int i = 0; i < 4; i++) load_a(A[i], p0 + i * 128, p0 + i * 128 + 8192);
        }
      }
    }
    GSTAMP(1);
    const uint32_t ea = mapa(sb + GB_EMPTY, lane & 1);
    if (lane < 2 * G_NST) mbar_arrive_cluster(ea + 8 * (lane >> 1));
    const int gc = (cta - 64) >> 1;
    const int jn = args.first[gc + 1];
    int ji = args.first[gc];
    const uint64_t dsc = dsc_hi | (uint64_t)(((sb >> 4) & 0x3FFF) | ((8192 >> 4) << 16));
    uint32_t st = 0, ph = 0;
    bool loaded = false;
    const uint8_t *p0, *p1;
    int ad;
    auto skip = [&](uint32_t job) { return (job & 0x400F) == 15 && j + wg == 2; };
    auto set_a = [&](uint32_t job) {
      const int m16 = ((job >> 1) & 7) * 16 + j * 8 + warp - (skip(job) ? 4 : 0);
      const bool fin = job & 1;
      p0 = fin ? g_a + (size_t)m16 * A_TILE + ((job >> 8) & 127) * 2048 + t * 128 + g * 16
               : reinterpret_cast<const uint8_t*>(args.x) + (size_t)(m16 * 16 + g) * (DM * 2) + t * 16;
      p1 = p0 + (fin ? 512 : 8 * DM * 2);
      ad = fin ? 1024 : 64;
    };
    auto dep_ptr = [&](uint32_t job) { return (((job >> 8) & 127) < 64 ? g_fo : g_fh) + (((job >> 1) & 7) * 16 + j * 8 + warp - (skip(job) ? 4 : 0)) * FS; };
    auto dep_cnt = [&](uint32_t job) { return tag * (((job >> 8) & 127) < 64 ? 32u : 14u); };
    float acc[128];
    for (; ji < jn; ji++) {
      const uint32_t job = args.job[ji];
      if (!loaded) {
        if (job & 1) wait_count(dep_ptr(job), dep_cnt(job));
        set_a(job);
        load_a(A[0], p0, p1, ad); load_a(A[1], p0 + 2 * ad, p1 + 2 * ad, ad);
      }
      QSTAMP(16 + ji - args.first[gc], 0);
      const uint32_t nxt = args.job[ji + 1];
      const uint32_t dep = ld_relaxed(dep_ptr(nxt));
      const int nk = (job >> 15) & 127;
      uint32_t pst = 0;
      const unsigned* gp = g_gate + (((job >> 1) & 7) * 16 + j * 8 + warp) * 16 + g;
      uint32_t g0 = ld_relaxed(gp), g1 = ld_relaxed(gp + 8);
      if (wg == 1 && nk >= 8) bar_sync<2, 256>();
      for (int k = 0; k < nk; k += 2) {
        const uint32_t s0 = st, f0 = ph;
        if (++st == G_NST) { st = 0; ph ^= 1; }
        mbar_wait(sb + GB_FULL + 8 * s0, f0);
        wg_wait<1>();
        if (k != 0 && lane < 2) mbar_arrive_cluster(ea + 8 * (pst & 7));
        wg_wait<0>();
        frag_a(U[0], A[0], args.zero);
        frag_a(U[1], A[1], args.zero);
        uint64_t d = dsc + s0 * (G_ST >> 4);
        wg_fence();
        wgmma_rs256(acc, U[0][0], U[0][1], U[0][2], U[0][3], d, (k | (job & (1u << 24))) != 0);
        wgmma_rs256(acc, U[0][4], U[0][5], U[0][6], U[0][7], d + 64, 1);
        wgmma_rs256(acc, U[0][8], U[0][9], U[0][10], U[0][11], d + 256, 1);
        wgmma_rs256(acc, U[0][12], U[0][13], U[0][14], U[0][15], d + 320, 1);
        wg_commit();
        if (k != 0 && lane < 2) mbar_arrive_cluster(ea + 8 * (pst >> 3));
        p0 += 4 * ad; p1 += 4 * ad;
        if (k + 2 < nk) { load_a(A[0], p0, p1, ad); load_a(A[1], p0 + 2 * ad, p1 + 2 * ad, ad); }
        if (k + 2 + PF_A < nk && lane == 0 && (job & 1)) asm volatile("cp.async.bulk.prefetch.L2.global [%0], 4096;" :: "l"(p0 + PF_A * 2048) : "memory");
        mbar_wait(sb + GB_FULL + 8 * st, ph);
        d = dsc + st * (G_ST >> 4);
        wgmma_rs256(acc, U[1][0], U[1][1], U[1][2], U[1][3], d, 1);
        wgmma_rs256(acc, U[1][4], U[1][5], U[1][6], U[1][7], d + 64, 1);
        wgmma_rs256(acc, U[1][8], U[1][9], U[1][10], U[1][11], d + 256, 1);
        wgmma_rs256(acc, U[1][12], U[1][13], U[1][14], U[1][15], d + 320, 1);
        wg_commit();
        if (k == LAG_K && wg == 0 && nk >= 8) bar_arrive<2, 256>();
        pst = s0 | st << 3;
        if (++st == G_NST) { st = 0; ph ^= 1; }
      }
      wg_wait<1>();
      if (lane < 2) mbar_arrive_cluster(ea + 8 * (pst & 7));
      wg_wait<0>();
      QSTAMP(16 + ji - args.first[gc], 2);
      if (lane < 2) mbar_arrive_cluster(ea + 8 * (pst >> 3));
      check_gate(g0, g1, gp, tag);
      loaded = ji + 1 < jn && (!(nxt & 1) || (int)(dep - dep_cnt(nxt)) >= 0);
      if (loaded) {
        if (nxt & 1) fence_gpu();
        set_a(nxt);
        load_a(A[0], p0, p1, ad); load_a(A[1], p0 + 2 * ad, p1 + 2 * ad, ad);
      }
      QSTAMP(16 + ji - args.first[gc], 1);
      const int m16 = ((job >> 1) & 7) * 16 + j * 8 + warp, n = (job >> 4) & 15;
      const int row = m16 * 16 + g;
      if (!(job & 1)) {
        const float s0 = 1.0f - __uint_as_float(g0), s1 = 1.0f - __uint_as_float(g1);
        uint8_t* q = g_a + (size_t)m16 * A_TILE + (HD / 32 + n * 4) * 1024 + t * 128 + g * 16;
#pragma unroll
        for (int b = 0; b < 4; b++) {
          uint32_t lo[4], hi[4];
#pragma unroll
          for (int i = 0; i < 4; i++) {
            const float* ga = acc + 16 * b + 4 * i;
            float v[4];
#pragma unroll
            for (int e = 0; e < 4; e++) v[e] = __fdividef(ga[64 + e] * (e < 2 ? s0 : s1), 1.0f + ex2(ga[e] * -1.4426950408889634f));
            lo[i] = pack_bf16(v[0], v[1]); hi[i] = pack_bf16(v[2], v[3]);
          }
          *reinterpret_cast<uint4*>(q + 1024 * b) = make_uint4(lo[0], lo[1], lo[2], lo[3]);
          *reinterpret_cast<uint4*>(q + 1024 * b + 512) = make_uint4(hi[0], hi[1], hi[2], hi[3]);
        }
        QSTAMP(16 + ji - args.first[gc], 4);
        publish();
      } else {
        const uint32_t mode = (job >> 22) & 3, parts = job >> 25;
        float4* q = reinterpret_cast<float4*>(g_acc) + (m16 * 2 + n) * 1024;
        if (mode == M_STORE) {
#pragma unroll
          for (int i = 0; i < 32; i++) q[i * 32 + lane] = make_float4(acc[4 * i], acc[4 * i + 1], acc[4 * i + 2], acc[4 * i + 3]);
          publish();
        } else if (mode == M_RED) {
          const unsigned* fc = g_fc + (m16 * 2 + n) * FS;
          if (!skip(job)) {
            wait_count(fc, (tag - 1) * (parts + 1) + 1);
#pragma unroll
            for (int i = 0; i < 32; i++) red4(q + i * 32 + lane, acc + 4 * i);
            publish();
          }
          wait_count(fc, tag * (skip(job) ? NH + 1 : parts + 1));
          for (int r = ((job >> 8) & 63) >> 2, e = r + (nk >> 2); r < e; r++) {
            const int i = (r >> 3) * 16 + (lane >> 1);
            const float4 u = __ldcg(q + i * 32 + (r & 7) * 4 + (lane & 1) * 2), v = __ldcg(q + i * 32 + (r & 7) * 4 + (lane & 1) * 2 + 1);
            uint2* o = reinterpret_cast<uint2*>(args.out + (size_t)(m16 * 16 + (r & 7)) * DM + n * 256 + (r >> 3) * 128) + lane;
            o[0] = make_uint2(pack_bf16(u.x, u.y), pack_bf16(v.x, v.y));
            o[2 * DM] = make_uint2(pack_bf16(u.z, u.w), pack_bf16(v.z, v.w));
          }
        } else if (mode == M_OUT) {
          uint32_t* o = reinterpret_cast<uint32_t*>(args.out + (size_t)row * DM + n * 256) + t;
#pragma unroll
          for (int i = 0; i < 32; i++) { o[4 * i] = pack_bf16(acc[4 * i], acc[4 * i + 1]); o[4 * i + 4 * DM] = pack_bf16(acc[4 * i + 2], acc[4 * i + 3]); }
        }
      }
      GSTAMP(2 + ji - args.first[gc]);
      QSTAMP(16 + ji - args.first[gc], 3);
    }
    asm volatile("barrier.cluster.arrive.aligned; barrier.cluster.wait.aligned;" ::: "memory");
  } else if (cta >= 64) {
    auto load_w = [&](int u) {
      const int b = (u + 1) % 3, i = u / 3;
      tma5d(sb + b * 65536 + i * 16384, &args.pw[b], h * DH + j * 64, 4 * i, sb + GB_W + 8 * i);
    };
    if (warp == 9 && lane == 0 && cta < 128) {
      for (int i = 0; i < 4; i++) mbar_init(sb + GB_W + 8 * i, 1);
      asm volatile("fence.mbarrier_init.release.cluster; fence.proxy.async.shared::cta;" ::: "memory");
      for (int i = 0; i < 4; i++) mbar_expect_tx(sb + GB_W + 8 * i, 49152);
      for (int u = 0; u < EARLY_W; u++) load_w(u);
    }
    __syncwarp();
    start();
    asm volatile("setmaxnreg.dec.sync.aligned.u32 40;");
    if (warp == 9 && lane == 0 && cta < 128) {
      for (int u = EARLY_W; u < 12; u++) load_w(u);
    } else if (warp == 8 && lane == 0) {
      const int gc = (cta - 64) >> 1;
      const int jn = args.first[gc + 1];
      uint32_t st = 0, ph = 0;
      for (int ji = args.first[gc]; ji < jn; ji++) {
        const uint32_t job = args.job[ji];
        const int n = (job >> 4) & 15, k0 = (job >> 8) & 127, nk = (job >> 15) & 127;
        const CUtensorMap* tm = &args.pb[(job & 1) ? (k0 < 64 ? 2 : 3) : j];
        const int col = (job & 1) ? n * 256 + j * 128 : n * 128;
        for (int k = 0; k < nk; k++) {
          mbar_wait_cluster(sb + GB_EMPTY + 8 * st, ph);
          const uint32_t mb = sb + GB_FULL + 8 * st, dst = sb + st * G_ST + j * 16384;
          mbar_expect_tx(mb, G_ST);
          tma5d_mc(dst, tm, col, 2 * ((k0 & 63) + k), mb);
          tma5d_mc(dst + 8192, tm, col + 64, 2 * ((k0 & 63) + k), mb);
          if (++st == G_NST) { st = 0; ph ^= 1; }
        }
      }
      atomicAdd(&g_done, 1u);
    } else if (warp > 9) {
      const int wg = warp - 10, gc = (cta - 64) >> 1;
      uint32_t ev = sb + GB_EV + wg * (8 * G_NEV);
      if (cta < 128)
        for (int it = 0; it < 16; it++, ev += 8) {
          if (lane == 0 && it + PF_X < 16) asm volatile("cp.async.bulk.prefetch.L2.global [%0], 1024;" :: "l"(args.x + ((it + PF_X) * 128 + wg * 64 + cta - 64) * DM) : "memory");
          mbar_wait(ev, 0);
          if (it < 2) { PSTAMP(320, 1 + 4 * it); PSTAMP(352, 3 + 4 * it); }
          fence_gpu();
          if (lane < 4) red_relaxed(g_fq + (4 * it + 2 * wg + (lane >> 1)) * NH + h);
          if (it < 2) { PSTAMP(320, 2 + 4 * it); PSTAMP(352, 4 + 4 * it); }
        }
      const int jn = args.first[gc + 1];
      for (int ji = args.first[gc]; ji < jn; ji++) {
        const uint32_t job = args.job[ji], mode = (job >> 22) & 3;
        if ((job & 1) && (mode == M_CONT || mode == M_OUT)) continue;
        if ((job & 0x400F) == 15 && j + wg == 2) continue;
        const int m16 = ((job >> 1) & 7) * 16 + j * 8 + wg * 4 + (lane & 3);
        mbar_wait(ev, 0);
        ev += 8;
        fence_gpu();
        if (lane < 4) red_relaxed((job & 1) ? g_fc + (m16 * 2 + ((job >> 4) & 15)) * FS : g_fh + m16 * FS);
      }
    }
    __syncwarp();
    asm volatile("barrier.cluster.arrive.aligned; barrier.cluster.wait.aligned;" ::: "memory");
  } else if (warp < 8) {
    const int gam = warp >> 2, w = warp & 3;
    uint32_t wq[16][4], wk[16][4], wv[16][4];
    const uint32_t l16 = __shfl_sync(~0u, lane * 16, lane);
    float fq, fk, fv;
    uint32_t p0[4], p1[4];
    {
      const uint32_t o = ((lane & 7) + ((lane >> 4) << 3)) * 128 + (((2 * w + ((lane >> 3) & 1)) ^ (lane & 7)) << 4) + gam * 16384 + (w << 12);
      auto load_w = [&](uint32_t (*W)[4], uint32_t base) {
        uint32_t m = 0;
#pragma unroll
        for (int i = 0; i < 16; i++) {
          ldm4t(W[i], base + (o ^ ((i >> 2) << 12)) + ((i >> 1) & 1) * 32768 + (i & 1) * 2048);
          m = absmax2(absmax2(m, absmax2(W[i][0], W[i][1])), absmax2(W[i][2], W[i][3]));
        }
        return __reduce_max_sync(~0u, fold_absmax(m));
      };
      auto to_f16 = [&](uint32_t (*W)[4], uint32_t m) {
        const uint32_t e = max(m >> 7, 15u);
        const uint32_t sc = (268u - e) * 0x00800080u;
#pragma unroll
        for (int i = 0; i < 64; i++) {
          uint32_t v;
          asm("mul.rn.bf16x2 %0, %1, %2;" : "=r"(v) : "r"(W[i >> 2][i & 3]), "r"(sc));
          W[i >> 2][i & 3] = pack_f16(bf_lo(v), bf_hi(v));
          asm volatile("" : "+r"(W[i >> 2][i & 3]));
        }
        return __uint_as_float((e - 14u) << 23);
      };
      uint32_t mm = 0;
      {
#pragma unroll
        for (int i = 0; i < 16; i++) *reinterpret_cast<uint4*>(wq[i]) = __ldg(reinterpret_cast<const uint4*>(args.mem0) + i * 32 + lane);
#pragma unroll
        for (int i = 0; i < 4; i++) {
          const uint32_t* mp = reinterpret_cast<const uint32_t*>(args.mem0 + (lane >> 2) * DM + warp * 32 + i * 8 + 2 * (lane & 3));
          p0[i] = __ldg(mp); p1[i] = __ldg(mp + 128);
        }
#pragma unroll
        for (int i = 0; i < 16; i++) mm = absmax2(mm, absmax2(absmax2(wq[i][0], wq[i][1]), absmax2(wq[i][2], wq[i][3])));
      }
      const int E0 = min(max((int)(__reduce_max_sync(~0u, fold_absmax(mm)) >> 7) - 141, -100), 100);
      sts32(sb + C_UP, (uint32_t)(127 + E0) << 23); sts32(sb + C_UP + 4, E0);
      start();
      PSTAMP(0, 2);
      if (tid == 0) {
        const int col = h * DH + j * 64;
        mbar_expect_tx(sb + MB_WV, 65536); mbar_expect_tx(sb + MB_WQ, 65536); mbar_expect_tx(sb + MB_WK, 65536);
        for (int i = 0; i < V_FIRST; i++) tma2d(sb + C_WO + i * 16384, &args.tmv, col, i * 128, sb + MB_WV);
        for (int i = 0; i < 4; i++) {
          if (i + V_FIRST < 4) tma2d(sb + C_WO + (i + V_FIRST) * 16384, &args.tmv, col, (i + V_FIRST) * 128, sb + MB_WV);
          tma2d(sb + C_SW + i * 16384, &args.tmq, col, i * 128, sb + MB_WQ);
          tma2d(sb + C_KVQ + i * 16384, &args.tmk, col, i * 128, sb + MB_WK);
        }
      }
      __syncwarp();
      const float dn = __uint_as_float((uint32_t)(127 - E0) << 23);
#pragma unroll
      for (int i = 0; i < 4; i++) {
        p0[i] = pack_f16(bf_lo(p0[i]) * dn, bf_hi(p0[i]) * dn);
        p1[i] = pack_f16(bf_lo(p1[i]) * dn, bf_hi(p1[i]) * dn);
      }
      asm volatile("setmaxnreg.inc.sync.aligned.u32 " FAT_REGS ";");
      PSTAMP(0, 3);
      mbar_wait(sb + MB_WV, 0);
      PSTAMP(0, 4);
      const uint32_t mv = load_w(wv, sb + C_WO);
      if (lane == 0) sts32(sb + C_WM + warp * 4, mv);
      bar_arrive<10, 384>();
      fv = to_f16(wv, mv);
      PSTAMP(0, 5);
      mbar_wait(sb + MB_WQ, 0);
      fq = to_f16(wq, load_w(wq, sb + C_SW));
      PSTAMP(0, 6);
      mbar_wait(sb + MB_WK, 0);
      PSTAMP(0, 7);
      const uint32_t mk = load_w(wk, sb + C_KVQ);
      bar_sync<11, 288>();
      fk = to_f16(wk, mk);
#pragma unroll
      for (int i = 0; i < 8; i++) {
        sts128(sb + C_SW + warp * 8192 + i * 1024 + l16, wq[i][0], wq[i][1], wq[i][2], wq[i][3]);
        sts128(sb + C_SW + warp * 8192 + i * 1024 + 512 + l16, wk[i][0], wk[i][1], wk[i][2], wk[i][3]);
      }
      PSTAMP(0, 8);
      mbar_wait(sb + MB_WO, 0);
      PSTAMP(0, 9);
      const uint32_t a = C_WO + (warp >> 1) * 16384 + ((lane & 7) + ((lane >> 4) << 3)) * 128 + ((((warp & 1) * 4 + ((lane >> 3) & 1)) ^ (lane & 7)) << 4);
#pragma unroll
      for (int i = 0; i < 8; i++) { ldm4t(wq[i], sb + a + (i << 11)); ldm4t(wk[i], sb + (a ^ 32) + (i << 11)); }
      uint32_t mo = 0;
#pragma unroll
      for (int i = 0; i < 32; i++) mo = absmax2(mo, absmax2(wq[i >> 2][i & 3], wk[i >> 2][i & 3]));
      sts32(sb + C_WM + 32 + ((fresh(threadIdx.x) >> 3) & ~3), __reduce_max_sync(~0u, fold_absmax(mo)));
      bar_sync<13, 288>();
#pragma unroll
      for (int i = 0; i < 8; i++) {
        sts128(sb + C_WO + warp * 8192 + i * 1024 + l16, wq[i][0], wq[i][1], wq[i][2], wq[i][3]);
        sts128(sb + C_WO + warp * 8192 + i * 1024 + 512 + l16, wk[i][0], wk[i][1], wk[i][2], wk[i][3]);
      }
#pragma unroll
      for (int i = 0; i < 8; i++) { lds128r(wq[i], sb + C_SW + warp * 8192 + i * 1024 + l16); lds128r(wk[i], sb + C_SW + warp * 8192 + i * 1024 + 512 + l16); }
    }
    const uint32_t peer = mapa(sb, j ^ 1);
    const uint32_t sw = sb + warp * 8192 - w * 1024, so = sb - w * 1024;
    const uint32_t rw = (uint32_t)(uintptr_t)ring + (w >> 1) * 8192 + (gam ^ (w >> 1)) * 4096 + (w & 1) * 2048, rh = (uint32_t)((uintptr_t)ring >> 32);
    const int delay = POLL_DELAY;
    const uint32_t mb = sb + C_MEM + gam * 4096;
    PSTAMP(0, 10);
    const uint32_t ma = __shfl_sync(~0u, w * 1024 + lane * 16, lane);
    for (int s = 0;; s++) {
      const uint32_t sz = s & args.zero;
      sts128(mb + ma, p0[0], p0[1], p0[2], p0[3]);
      sts128(mb + 512 + ma, p1[0], p1[1], p1[2], p1[3]);
      asm volatile("{ .reg .pred p; setp.ne.u32 p, %0, 0; @p bar.sync 4, 128; @!p bar.sync 3, 128; }" :: "r"(gam) : "memory");
      float cq[4], ck[4], cw[4], cx[4];
      uint32_t b[8][4], Wo[16][4];
      hma16z(ck, wk[0], p0[0], p0[1]);
      hma16z(cq, wq[0], p0[0], p0[1]);
      hma16z(cx, wk[1], p0[2], p0[3]);
      hma16z(cw, wq[1], p0[2], p0[3]);
      ldv_s(b[2], mb + (ma ^ 1024)); ldv_s(b[3], mb + 512 + (ma ^ 1024));
      FENCE_BB;
      hma16(ck, wk[2], p1[0], p1[1]);
      hma16(cq, wq[2], p1[0], p1[1]);
      hma16(cx, wk[3], p1[2], p1[3]);
      hma16(cw, wq[3], p1[2], p1[3]);
#pragma unroll
      for (int i = 4; i < 6; i++) ldv_s(b[i], mb + (i & 1) * 512 + ((ma | sz) ^ ((i >> 1) * 1024)));
      FENCE_BB;
      hma16(ck, wk[4], b[2][0], b[2][1]);
      hma16(cq, wq[4], b[2][0], b[2][1]);
      hma16(cx, wk[5], b[2][2], b[2][3]);
      hma16(cw, wq[5], b[2][2], b[2][3]);
#pragma unroll
      for (int i = 6; i < 8; i++) ldv_s(b[i], mb + (i & 1) * 512 + ((ma | sz) ^ ((i >> 1) * 1024)));
      FENCE_BB;
      uint32_t mx = absmax2h(absmax2h(absmax2h(p0[0], p0[1]), absmax2h(p0[2], p0[3])), absmax2h(absmax2h(p1[0], p1[1]), absmax2h(p1[2], p1[3])));
      mx = __reduce_max_sync(~0u, absmax2h(mx, mx << 16) & 0x7FFFFFFFu);
#pragma unroll
      for (int i = 3; i < WO_AT; i++) {
        hma16(ck, wk[2 * i], b[i][0], b[i][1]);
        hma16(cq, wq[2 * i], b[i][0], b[i][1]);
        hma16(cx, wk[2 * i + 1], b[i][2], b[i][3]);
        hma16(cw, wq[2 * i + 1], b[i][2], b[i][3]);
      }
      const uint32_t lw = ma | (b[5][0] & b[6][0] & b[7][0] & args.zero);
      FENCE_BB;
      const float up = __uint_as_float(lds32(sb + C_UP));
      sts32(sb + C_MX + warp * 4, mx);
#pragma unroll
      for (int u = 0; u < WO_QK; u++) ldv_s(Wo[u], sw + C_WO + u * 512 + lw);
      FENCE_BB;
#pragma unroll
      for (int i = WO_AT; i < 8; i++) {
        hma16(ck, wk[2 * i], b[i][0], b[i][1]);
        hma16(cq, wq[2 * i], b[i][0], b[i][1]);
        hma16(cx, wk[2 * i + 1], b[i][2], b[i][3]);
        hma16(cw, wq[2 * i + 1], b[i][2], b[i][3]);
      }
      const float uq = up * fq, uk = up * fk;
      stm4(sb + C_QM + gam * 512 + lw, pack_bf16((cq[0] + cw[0]) * uq, (cq[1] + cw[1]) * uq), pack_bf16((cq[2] + cw[2]) * uq, (cq[3] + cw[3]) * uq),
           pack_bf16((ck[0] + cx[0]) * uk, (ck[1] + cx[1]) * uk), pack_bf16((ck[2] + cx[2]) * uk, (ck[3] + cx[3]) * uk));
      bar_arrive<6, 384>();
      FENCE_BB;
      hma16z(cq, wv[0], p0[0], p0[1]);
      hma16z(cw, wv[1], p0[2], p0[3]);
      hma16z(ck, wv[2], p1[0], p1[1]);
      hma16z(cx, wv[3], p1[2], p1[3]);
#pragma unroll
      for (int i = 2; i < 8; i += 2) {
        hma16(cq, wv[2 * i], b[i][0], b[i][1]);
        hma16(cw, wv[2 * i + 1], b[i][2], b[i][3]);
        hma16(ck, wv[2 * i + 2], b[i + 1][0], b[i + 1][1]);
        hma16(cx, wv[2 * i + 3], b[i + 1][2], b[i + 1][3]);
      }
      {
        const float uv = up * fv;
        const uint32_t lo = pack_bf16(((cq[0] + cw[0]) + (ck[0] + cx[0])) * uv, ((cq[1] + cw[1]) + (ck[1] + cx[1])) * uv);
        const uint32_t hi = pack_bf16(((cq[2] + cw[2]) + (ck[2] + cx[2])) * uv, ((cq[3] + cw[3]) + (ck[3] + cx[3])) * uv);
        const uint32_t a = C_VM + (s & 1) * 4096 + j * 2048 + gam * 256 + (lw >> 1);
        st_async64(peer + a, lo, hi, peer + MB_V);
        sts64(sb + a, lo, hi);
        __syncwarp();
        asm volatile("{ .reg .pred p; setp.eq.u32 p, %1, 0; @p mbarrier.arrive.shared::cta.b64 _, [%0]; }" :: "r"(sb + MB_V), "r"(ma & 0x1F0) : "memory");
      }
      if (s == NSEG - 1) break;
#pragma unroll
      for (int u = WO_QK; u < WO_EARLY; u++)
        ldv_s(Wo[u], sw + C_WO + u * 512 + (ma | (u >= WO_QK + WO_PAR ? Wo[u - WO_PAR][0] & args.zero : 0u)));
      const uint32_t lb = ma | sz;
      const uint32_t rp = rw + (s & 7) * RING_SLOT;
      const uint32_t o16 = fresh(rp + j * 16384 + (lb & 0x70) + (lb & 0x80) * 2 + (lb & 0x100) * 4);
      const uint32_t o4 = fresh(rp + 128 + ((lb >> 3) & 0x1C) + (lb & 0x100) * 4 + ((~lb & 16) << 10));
      const uint32_t sa = fresh(lb & 0x30);
      FENCE_BB;
      bar_sync<7, 384>();
      ldm4t(b[0], so + C_OT + ma); ldm4t(b[1], so + C_OT + 512 + ma);
      const float2 su = lds64f(sb + C_SU + sa);
      ldm4t(b[2], so + C_OT + 1024 + ma);
      FENCE_BB;
      mma16z(cx, Wo[3][0], Wo[3][1], Wo[3][2], Wo[3][3], b[0][2], b[0][3]);
      mma16z(ck, Wo[1][0], Wo[1][1], Wo[1][2], Wo[1][3], b[0][0], b[0][1]);
      mma16z(cw, Wo[2][0], Wo[2][1], Wo[2][2], Wo[2][3], b[0][2], b[0][3]);
      mma16z(cq, Wo[0][0], Wo[0][1], Wo[0][2], Wo[0][3], b[0][0], b[0][1]);
      FENCE_BB;
      ldm4t(b[3], so + C_OT + 1536 + ma);
      const float r0 = rcp(su.x), r1 = rcp(su.y);
      const uint32_t sel = ((o16 ^ o4) & 16384) ? 0x3210 : 0x5410;
      Wo[12][0] |= __float_as_uint(r0) & __float_as_uint(r1) & sel & args.zero;
#pragma unroll
      for (int k = 1; k < 4; k++) {
        mma16(cq, Wo[4 * k][0], Wo[4 * k][1], Wo[4 * k][2], Wo[4 * k][3], b[k][0], b[k][1]);
        mma16(ck, Wo[4 * k + 1][0], Wo[4 * k + 1][1], Wo[4 * k + 1][2], Wo[4 * k + 1][3], b[k][0], b[k][1]);
        mma16(cw, Wo[4 * k + 2][0], Wo[4 * k + 2][1], Wo[4 * k + 2][2], Wo[4 * k + 2][3], b[k][2], b[k][3]);
        mma16(cx, Wo[4 * k + 3][0], Wo[4 * k + 3][1], Wo[4 * k + 3][2], Wo[4 * k + 3][3], b[k][2], b[k][3]);
      }
      {
        const uint32_t u3 = movm(pack_f16((ck[2] + cx[2]) * r0, (ck[3] + cx[3]) * r1));
        const uint32_t u0 = movm(pack_f16((cq[0] + cw[0]) * r0, (cq[1] + cw[1]) * r1)), u1 = movm(pack_f16((cq[2] + cw[2]) * r0, (cq[3] + cw[3]) * r1));
        const uint32_t u2 = movm(pack_f16((ck[0] + cx[0]) * r0, (ck[1] + cx[1]) * r1));
        asm volatile("red.relaxed.gpu.global.add.noftz.v4.f16x2 [%0], {%1,%2,%3,%4};"
                     :: "l"(gptr(o16, rh)), "r"(u0), "r"(u1), "r"(u2), "r"(__byte_perm(u3, 0x3C00u, sel)) : "memory");
        asm volatile("{ .reg .pred p; setp.eq.u32 p, %2, 0x5410; @p red.relaxed.gpu.global.add.noftz.f16x2 [%0], %1; }"
                     :: "l"(gptr(o4, rh)), "r"(__byte_perm(u3, 0x3C00u, 0x5432)), "r"(sel) : "memory");
      }
      bar_arrive<9, 384>();
      uint32_t z = 0;
#pragma unroll
      for (int i = 0; i < WV_A; i++) {
        uint32_t* d = (i & 1) ? wk[i >> 1] : wq[i >> 1];
        ldv_s(d, sw + C_SW + i * 512 + (ma | z));
        z = d[0] & args.zero;
      }
#pragma unroll 1
      for (int i = 0; i < delay; i++) z = __shfl_sync(~0u, z, 0);
      const uint8_t* const pa = gptr((o16 & ~16384u) | z, rh);
      uint4 a0 = ldv128(pa), a1 = ldv128(pa + 16384);
      uint32_t b0 = ldv32(gptr(o4, rh));
#pragma unroll
      for (int i = WV_A; i < 16; i++) ldv_s((i & 1) ? wk[i >> 1] : wq[i >> 1], sw + C_SW + i * 512 + ma);
      const bool odd = (o4 & 16384) == 0;
      const uint32_t sel0 = fresh(odd ? 0x5410 : 0x3210), sel1 = fresh(sel0 ^ 0x6600);
      FENCE_BB;
      if (__builtin_expect(__any_sync(~0u, (~((odd ? a0.w : a1.w) & b0) & 0x50000000u) != 0), 0)) {
        int it = 0;
        do {
          a0 = ldv128(pa); a1 = ldv128(pa + 16384); b0 = ldv32(gptr(o4, rh));
        } while (__any_sync(~0u, (~((odd ? a0.w : a1.w) & b0) & 0x50000000u) != 0) && ++it < 65536);
      }
      p0[0] = a0.x; p0[1] = a0.y; p0[2] = a0.z; p0[3] = prmt(a0.w, b0, sel0);
      p1[0] = a1.x; p1[1] = a1.y; p1[2] = a1.z; p1[3] = prmt(a1.w, b0, sel1);
    }
    if (!SKIP_LAST) bar_arrive<7, 384>();
    bar_arrive<9, 384>();
    {
      const int ln = fresh(threadIdx.x) & 31;
      uint32_t Wo[16][4];
#pragma unroll
      for (int u = 0; u < 16; u++) lds128r(Wo[u], sb + C_WO + warp * 8192 + u * 512 + ln * 16);
      unsigned* fc = g_fc + ((124 + (ln & 3)) * 2 + j) * FS;
      wait_count(fc, (lds32(sb + K_TAG) - 1) * (NH + 1) + 1);
#pragma unroll 1
      for (int u = 0; u < 2; u++) {
#pragma unroll
        for (int v = 0; v < 2; v++) {
          if (v == 0 && u == 1) bar_sync<13, 384>();
          else mbar_wait(sb + MB_WQ + 8 * u, 1);
          const uint32_t src = sb + C_KVQ + (v ? KVQ_ST + 4096 + u * 4096 : (2 - 2 * u) * KVQ_ST + j * 16384)
                               + ((ln >> 3) & 1) * 512 + (ln >> 4) * 128 + (ln & 7) * 16;
          float c[4][4];
#pragma unroll
          for (int k = 0; k < 8; k++) {
            uint32_t a[4];
            ldm4(a, src + (k >> 1) * 1024 + (k & 1) * 256);
#pragma unroll
            for (int i = 0; i < 4; i++) {
              const uint32_t* b = Wo[2 * k + (i >> 1)] + (i & 1);
              if (k == 0) mma16z(c[i], a[0], a[1], a[2], a[3], b[0], b[2]);
              else mma16(c[i], a[0], a[1], a[2], a[3], b[0], b[2]);
            }
          }
          float4* q = reinterpret_cast<float4*>(g_acc) + ((124 + 2 * u + (j ^ v)) * 2 + j) * 1024 + warp * 128 + ln;
#pragma unroll
          for (int i = 0; i < 4; i++) red4(q + i * 32, c[i]);
        }
      }
      asm volatile("barrier.cluster.arrive.relaxed.aligned;" ::: "memory");
      bar_sync<12, 256>();
      if (warp == 0) {
        fence_gpu();
        if (ln < 4) red_relaxed(fc);
      }
      __syncwarp();
      asm volatile("barrier.cluster.wait.aligned;" ::: "memory");
    }
  } else {
    const int w = warp - 8, at = tid - 256;
    uint32_t tag;
    {
      uint32_t mx = 0, gw[8], a[8][8];
      float acc[8];
      const int tok = cta * SEGL + w * 8;
      const uint8_t* xr = reinterpret_cast<const uint8_t*>(args.x + (size_t)tok * DM) + lane * 16;
#pragma unroll
      for (int r = 0; r < 8; r++) { ldg128(a[r], xr + r * 1024); ldg128(a[r] + 4, xr + r * 1024 + 512); }
      ldg128(gw, reinterpret_cast<const uint8_t*>(args.gate_w) + lane * 16); ldg128(gw + 4, reinterpret_cast<const uint8_t*>(args.gate_w) + 512 + lane * 16);
#pragma unroll
      for (int r = 0; r < 8; r++) {
        acc[r] = 0.f;
#pragma unroll
        for (int i = 0; i < 8; i++) { acc[r] += bf_lo(a[r][i]) * bf_lo(gw[i]) + bf_hi(a[r][i]) * bf_hi(gw[i]); mx = absmax2(mx, a[r][i]); }
      }
      mx = __reduce_max_sync(~0u, fold_absmax(mx));
      sts32(sb + C_WM + 64 + w * 4, mx);
      tag = start();
      asm volatile("setmaxnreg.dec.sync.aligned.u32 " AUX_REGS ";"
                   : "+f"(acc[0]), "+f"(acc[1]), "+f"(acc[2]), "+f"(acc[3]), "+f"(acc[4]), "+f"(acc[5]), "+f"(acc[6]), "+f"(acc[7]));
#pragma unroll
      for (int o = 16; o; o >>= 1)
#pragma unroll
        for (int r = 0; r < 8; r++) acc[r] += __shfl_xor_sync(~0u, acc[r], o);
#pragma unroll
      for (int r = 1; r < 8; r++) acc[0] = lane == r ? acc[r] : acc[0];
      if (lane < 8) st_relaxed(g_gate + tok + lane, (__float_as_uint(__fdividef(1.0f, 1.0f + __expf(-acc[0]))) & ~15u) | (tag & 15));
    }
    PSTAMP(320, 1);
    bar_sync<10, 384>();
    if (w == 0) {
      if (at == 0) {
        mbar_expect_tx(sb + MB_WO, 65536);
        for (int i = 0; i < 4; i++) tma2d(sb + C_WO + i * 16384, &args.tmo, j * 256 + i * 64, h * DH, sb + MB_WO);
      }
      __syncwarp();
      bar_sync<13, 288>();
      const uint32_t m = lds32(sb + C_WM + min(lane, 19) * 4) >> 7;
      const uint32_t mv = __reduce_max_sync(~0u, lane < 8 ? m : 0), mo = __reduce_max_sync(~0u, (lane >> 3) == 1 ? m : 0), mx = __reduce_max_sync(~0u, lane < 16 ? 0 : m);
      if (at == 0) asm volatile("st.volatile.global.v4.u32 [%0], {%1,%2,%3,%4};" :: "l"(&g_pub[cta]), "r"(tag), "r"(mx), "r"(mv), "r"(mo) : "memory");
    } else if (w == 2) {
      uint4 r0, r1;
      int it = 0;
      while (true) {
        r0 = ldv128(&g_pub[lane]); r1 = ldv128(&g_pub[lane + 32]);
        if (__all_sync(~0u, r0.x == tag && r1.x == tag)) break;
        if (give_up(++it, 4)) break;
      }
      PSTAMP(320, 11);
      sts32(sb + C_XE + lane * 4, r0.y); sts32(sb + C_XE + 128 + lane * 4, r1.y);
      sts32(sb + C_WE, __reduce_max_sync(~0u, max(r0.z, r1.z)) + __reduce_max_sync(~0u, max(r0.w, r1.w)) - 3 * 126 + 21 - 14);
    } else if (w == 3) {
      bar_sync<11, 288>();
      wait_count(g_fq + (lane & 1) * NH + h, tag * 4);
      asm volatile("fence.proxy.async.global;" ::: "memory");
      if (lane == 0) { issue_stage(0, 0); issue_stage(1, 1); }
    }
    __syncwarp();
    const uint32_t peer = mapa(sb, j ^ 1);
    const float SC = 0.08838834764831845f * 1.4426950408889634f;
    const uint32_t ONE = 0x3F803F80u;
    int st = 0, stp = 0;
    bool late = false;
    auto scores = [&](int sg, int stg, int par) {
      const uint32_t l16 = fresh(lane) * 16;
      const uint32_t kv = sb + C_KVQ + stg * KVQ_ST + (j ? 0 : 4096), qx = sb + C_KVQ + stg * KVQ_ST + (j ? 16384 : 0);
      mbar_wait1(sb + MB_KVQ + 8 * stg, par);
      float sc[4][4];
#pragma unroll
      for (int i = 0; i < 4; i++) {
        uint32_t a[4], c[4], kb[4][4];
        lds128r(a, qx + i * 1024 + l16);
        lds128r(kb[0], kv + i * 512 + l16); lds128r(kb[1], kv + 2048 + i * 512 + l16);
        lds128r(c, qx + i * 1024 + 512 + l16);
        lds128r(kb[2], kv + 4096 + i * 512 + l16); lds128r(kb[3], kv + 6144 + i * 512 + l16);
#pragma unroll
        for (int n = 0; n < 4; n++) {
          if (i == 0) mma16z(sc[n], a[0], a[1], a[2], a[3], kb[n][0], kb[n][1]);
          else mma16(sc[n], a[0], a[1], a[2], a[3], kb[n][0], kb[n][1]);
        }
#pragma unroll
        for (int n = 0; n < 4; n++) mma16(sc[n], c[0], c[1], c[2], c[3], kb[n][2], kb[n][3]);
      }
      const float NEG = -1.0e9f * 1.4426950408889634f;
      const int d = 16 * j + (int)(l16 >> 6) - (int)((l16 >> 3) & 6);
#pragma unroll
      for (int n = 0; n < 4; n++)
        sts128(sb + C_SX + (sg & 1) * 2048 + n * 512 + l16, __float_as_uint(d >= 8 * n ? sc[n][0] * SC : NEG), __float_as_uint(d >= 8 * n + 1 ? sc[n][1] * SC : NEG),
               __float_as_uint(d >= 8 * n - 8 ? sc[n][2] * SC : NEG), __float_as_uint(d >= 8 * n - 7 ? sc[n][3] * SC : NEG));
    };
    if (w == 1) scores(0, 0, 0);
    PSTAMP(352, 12);
    int E = (int)lds32(sb + C_UP + 4);
    for (int s = 0; s < NSEG; s++) {
      const uint32_t l16 = fresh(lane) * 16;
      const uint32_t kv = sb + C_KVQ + st * KVQ_ST + (j ? 0 : 4096), qx = sb + C_KVQ + st * KVQ_ST + (j ? 16384 : 0);
      uint32_t fq = 0;
      if (w == 3) fq = ld_relaxed(g_fq + min(s + 2, NSEG - 1) * NH + h + (lane & args.zero));
      mbar_wait1(sb + MB_KVQ + 8 * st, stp);
      if (s == 0) { PSTAMP(352, 13); }
      if (s == 1) { PSTAMP(352, 14); }
      uint32_t va[4][4], vm[2][4], ks0, ks1;
      uint32_t vm_a = C_VM + (s & 1) * 4096 + w * 1024 + (l16 >> 1);
      {
        uint32_t ka[4], kc[4], kb[2][4], q[4][4], kk[4];
        lds128r(ka, kv + w * 2048 + j * 1024 + (w >> 1) * 512 + l16);
        lds128r(kc, kv + w * 2048 + j * 1024 + 512 - (w >> 1) * 512 + l16);
#pragma unroll
        for (int i = 0; i < 4; i++) lds128r(va[i], kv + 8192 + w * 2048 + i * 512 + l16);
#pragma unroll
        for (int i = 0; i < 4; i++) {
          kb[0][i] = (w & 1) ? ka[i ^ 2] : ka[i]; kb[1][i] = (w & 1) ? kc[i ^ 2] : kc[i];
          asm volatile("" : "+r"(kb[0][i]), "+r"(kb[1][i]));
        }
        uint32_t q_a = w * 512 + l16, r_a = peer + C_SR + (q_a >> 1);
        uint32_t q_0 = w * 1024 + (l16 & 0x70) + (l16 & 0x80) * 4 + ((l16 >> 1) & 0x80), q_1 = q_0 ^ 1024, q_2 = q_0 ^ 2048, q_3 = q_0 ^ 3072;
        asm volatile("" : "+r"(q_0), "+r"(q_1), "+r"(q_2), "+r"(q_3), "+r"(r_a), "+r"(vm_a));
        if (__builtin_expect(SKIP_LAST && s == NSEG - 1, 0)) {
          bar_sync<6, 384>();
          ldm4t(kk, sb + C_QM + 256 + q_0);
          ks0 = hadd2(kk[0], kk[1]); ks1 = hadd2(kk[2], kk[3]);
          mbar_wait1(sb + MB_V, s & 1);
          lds64r(vm[0], sb + vm_a); lds64r(vm[0] + 2, sb + vm_a + 256); lds64r(vm[1], sb + vm_a + 512); lds64r(vm[1] + 2, sb + vm_a + 768);
        } else {
        FENCE_BB;
        bar_sync<6, 384>();
        float s0[4], s1[4], s2[4];
        ldm4t(q[0], sb + C_QM + q_0); ldm4t(q[1], sb + C_QM + q_1); ldm4t(kk, sb + C_QM + 256 + q_0); ldm4t(q[2], sb + C_QM + q_2); ldm4t(q[3], sb + C_QM + q_3);
        FENCE_BB;
        mma16z(s0, q[0][0], q[0][1], q[0][2], q[0][3], kb[0][0], kb[0][1]);
        mma16z(s1, q[1][0], q[1][1], q[1][2], q[1][3], kb[0][2], kb[0][3]);
        ks0 = hadd2(kk[0], kk[1]); ks1 = hadd2(kk[2], kk[3]);
        mma16z(s2, q[0][0], q[0][1], q[0][2], q[0][3], ks0, ks1);
        mma16(s0, q[2][0], q[2][1], q[2][2], q[2][3], kb[1][0], kb[1][1]);
        mma16(s1, q[3][0], q[3][1], q[3][2], q[3][3], kb[1][2], kb[1][3]);
        const float x2 = s2[0] + s2[2], x3 = s2[1] + s2[3];
        const float x0 = (s0[0] + s0[2]) + (s1[0] + s1[2]), x1 = (s0[1] + s0[3]) + (s1[1] + s1[3]);
        st_async64(r_a, pack_bf16(x0, x1), pack_bf16(x2, x3), peer + MB_S);
        FENCE_BB;
        sts128(sb + C_SL + q_a, __float_as_uint(x0), __float_as_uint(x1), __float_as_uint(x2), __float_as_uint(x3));
        const uint4 ma = lds128(sb + C_MX), mc = lds128(sb + C_MX + 16);
        const int xe = lds32(sb + C_XE + s * 4), we = lds32(sb + C_WE);
        bar_sync<8, 128>();
        float4 u[4];
#pragma unroll
        for (int i = 0; i < 4; i++) u[i] = lds128f(sb + C_SL + i * 512 + l16);
        const bool s_ok = mbar_try(sb + MB_S, s & 1);
        FENCE_BB;
        E = max((int)(max(max(max(ma.x, ma.y), max(ma.z, ma.w)), max(max(mc.x, mc.y), max(mc.z, mc.w))) >> 26) + 112 + E, xe) + we;
        E = min(max(E, -100), 100);
        float up = __uint_as_float((uint32_t)(127 + E) << 23);
        sts32(sb + C_UP, __float_as_uint(up));
        float z0 = (u[0].z + u[1].z) + (u[2].z + u[3].z), z1 = (u[0].w + u[1].w) + (u[2].w + u[3].w);
        asm volatile("" : "+f"(z0), "+f"(z1), "+f"(up));
        if (__builtin_expect(!s_ok, 0)) mbar_wait1(sb + MB_S, s & 1);
        uint2 r[4];
#pragma unroll
        for (int i = 0; i < 4; i++) r[i] = lds64(sb + C_SR + i * 256 + (l16 >> 1));
        const bool v_ok = mbar_try(sb + MB_V, s & 1);
        FENCE_BB;
        const uint32_t rm = hadd2(hadd2(r[0].y, r[1].y), hadd2(r[2].y, r[3].y));
        const float sv[10] = {u[0].x + bf_lo(r[0].x), u[0].y + bf_hi(r[0].x), u[1].x + bf_lo(r[1].x), u[1].y + bf_hi(r[1].x),
                              u[2].x + bf_lo(r[2].x), u[2].y + bf_hi(r[2].x), u[3].x + bf_lo(r[3].x), u[3].y + bf_hi(r[3].x),
                              z0 + bf_lo(rm), z1 + bf_hi(rm)};
        float m = fmaxf(fmaxf(fmaxf(sv[0], sv[1]), fmaxf(sv[2], sv[3])), fmaxf(fmaxf(sv[4], sv[5]), fmaxf(sv[6], sv[7])));
        m = fmaxf(m, fmaxf(sv[8], sv[9])) * SC;
        const float m1 = __shfl_xor_sync(~0u, m, 1), m2 = __shfl_xor_sync(~0u, m, 2), m3 = __shfl_xor_sync(~0u, m, 3);
        float e[10], o0[4], o1[4], o2[4], o3[4], su[4];
#pragma unroll
        for (int i = 0; i < 4; i++) e[i] = ex2v(fmaf(sv[i], SC, -m));
        FENCE_BB;
        const float c = ex2v(m - fmaxf(fmaxf(m, m1), fmaxf(m2, m3)));
#pragma unroll
        for (int i = 4; i < 10; i++) e[i] = ex2v(fmaf(sv[i], SC, -m));
        if (__builtin_expect(!v_ok, 0)) mbar_wait1(sb + MB_V, s & 1);
        lds64r(vm[0], sb + vm_a); lds64r(vm[0] + 2, sb + vm_a + 256); lds64r(vm[1], sb + vm_a + 512); lds64r(vm[1] + 2, sb + vm_a + 768);
        {
          const uint32_t pa = pack_bf16(e[0] * c, e[1] * c), pb = pack_bf16(e[2] * c, e[3] * c);
          const uint32_t pc = pack_bf16(e[4] * c, e[5] * c), pd = pack_bf16(e[6] * c, e[7] * c), pe = pack_bf16(e[8] * c, e[9] * c);
          mma16z(o0, va[0][0], va[0][1], va[0][2], va[0][3], pa, pb);
          mma16z(o1, va[2][0], va[2][1], va[2][2], va[2][3], pa, pb);
          mma16z(su, ONE, ONE, ONE, ONE, pa, pb);
          mma16z(o2, va[1][0], va[1][1], va[1][2], va[1][3], pc, pd);
          mma16z(o3, va[3][0], va[3][1], va[3][2], va[3][3], pc, pd);
          mma16(o0, vm[0][0], vm[0][1], vm[0][2], vm[0][3], pe, pe);
          mma16(o1, vm[1][0], vm[1][1], vm[1][2], vm[1][3], pe, pe);
          mma16(su, ONE, ONE, ONE, ONE, pc, pd);
          mma8(su, ONE, ONE, pe);
#pragma unroll
          for (int i = 0; i < 4; i++) { o0[i] += o2[i]; o1[i] += o3[i]; }
        }
        stm4(sb + C_OT + q_a, pack_bf16(o0[0], o0[1]), pack_bf16(o0[2], o0[3]), pack_bf16(o1[0], o1[1]), pack_bf16(o1[2], o1[3]));
        asm volatile("{ .reg .pred p; setp.lt.u32 p, %3, 64; @p st.shared.v2.f32 [%0], {%1,%2}; }"
                     :: "r"(sb + C_SU + q_a), "f"(su[0] * up), "f"(su[1] * up), "r"(q_a) : "memory");
        bar_arrive<7, 384>();
        }
        FENCE_BB;
        st_async64(r_a + (C_KX - C_SR) + j * 1024, ks0, ks1, peer + MB_K);
        sts64(sb + C_KX + j * 1024 + (q_a >> 1), ks0, ks1);
      }
      if (w == 0) {
        uint32_t g0 = ld_relaxed(g_gate + s * SEGL + 16 * j + (l16 >> 6)), g1 = ld_relaxed(g_gate + s * SEGL + 16 * j + 8 + (l16 >> 6));
        bar_sync<9, 384>();
        float sc[5][4], sd[4];
        mbar_wait1(sb + MB_K, s & 1);
#pragma unroll
        for (int i = 0; i < 4; i++) {
          uint32_t a[4], c[4], km[4];
          lds128r(a, qx + i * 1024 + l16); lds128r(c, qx + i * 1024 + 512 + l16);
          lds64r(km, sb + C_KX + i * 512 + (l16 >> 1)); lds64r(km + 2, sb + C_KX + i * 512 + 256 + (l16 >> 1));
          if (i == 0) { mma16z(sc[4], a[0], a[1], a[2], a[3], km[0], km[1]); mma16z(sd, c[0], c[1], c[2], c[3], km[2], km[3]); }
          else { mma16(sc[4], a[0], a[1], a[2], a[3], km[0], km[1]); mma16(sd, c[0], c[1], c[2], c[3], km[2], km[3]); }
        }
#pragma unroll
        for (int n = 0; n < 4; n++) *reinterpret_cast<float4*>(sc[n]) = lds128f(sb + C_SX + (s & 1) * 2048 + n * 512 + l16);
        if (l16 == 0 && s < NSEG - 1) mbar_expect_tx(sb + MB_K, 1024);
#pragma unroll
        for (int e = 0; e < 4; e++) sc[4][e] += sd[e];
#pragma unroll
        for (int e = 0; e < 4; e++) sc[4][e] *= SC;
        float x0 = fmaxf(sc[0][0], sc[0][1]), x1 = fmaxf(sc[0][2], sc[0][3]);
#pragma unroll
        for (int n = 1; n < 5; n++) { x0 = fmaxf(x0, fmaxf(sc[n][0], sc[n][1])); x1 = fmaxf(x1, fmaxf(sc[n][2], sc[n][3])); }
        x0 = fmaxf(x0, __shfl_xor_sync(~0u, x0, 1)); x1 = fmaxf(x1, __shfl_xor_sync(~0u, x1, 1));
        x0 = fmaxf(x0, __shfl_xor_sync(~0u, x0, 2)); x1 = fmaxf(x1, __shfl_xor_sync(~0u, x1, 2));
        float y0 = 0.f, y1 = 0.f;
#pragma unroll
        for (int n = 0; n < 5; n++) {
          sc[n][0] = ex2(sc[n][0] - x0); sc[n][1] = ex2(sc[n][1] - x0); sc[n][2] = ex2(sc[n][2] - x1); sc[n][3] = ex2(sc[n][3] - x1);
          y0 += sc[n][0] + sc[n][1]; y1 += sc[n][2] + sc[n][3];
        }
        y0 += __shfl_xor_sync(~0u, y0, 1); y1 += __shfl_xor_sync(~0u, y1, 1);
        y0 += __shfl_xor_sync(~0u, y0, 2); y1 += __shfl_xor_sync(~0u, y1, 2);
        check_gate(g0, g1, g_gate + s * SEGL + 16 * j + (l16 >> 6), tag);
        const float r0 = rcp(y0) * __uint_as_float(g0), r1 = rcp(y1) * __uint_as_float(g1);
        sts128(kv + l16, pack_bf16(sc[0][0] * r0, sc[0][1] * r0), pack_bf16(sc[1][0] * r0, sc[1][1] * r0),
               pack_bf16(sc[2][0] * r0, sc[2][1] * r0), pack_bf16(sc[3][0] * r0, sc[3][1] * r0));
        sts128(kv + 512 + l16, pack_bf16(sc[0][2] * r1, sc[0][3] * r1), pack_bf16(sc[1][2] * r1, sc[1][3] * r1),
               pack_bf16(sc[2][2] * r1, sc[2][3] * r1), pack_bf16(sc[3][2] * r1, sc[3][3] * r1));
        sts64(kv + 1024 + (l16 >> 1), pack_bf16(sc[4][0] * r0, sc[4][1] * r0), pack_bf16(sc[4][2] * r1, sc[4][3] * r1));
#pragma unroll
        for (int i = 0; i < 4; i++) lds128r(va[i], kv + 8192 + i * 512 + l16);
        lds64r(vm[0], sb + vm_a); lds64r(vm[0] + 2, sb + vm_a + 256); lds64r(vm[1], sb + vm_a + 512); lds64r(vm[1] + 2, sb + vm_a + 768);
      } else if (w == 1) {
        bar_sync<9, 384>();
        if (s < NSEG - 1) scores(s + 1, st == 2 ? 0 : st + 1, st == 2 ? stp ^ 1 : stp);
#pragma unroll
        for (int i = 0; i < 4; i++) lds128r(va[i], kv + 10240 + i * 512 + l16);
        lds64r(vm[0], sb + vm_a); lds64r(vm[0] + 2, sb + vm_a + 256); lds64r(vm[1], sb + vm_a + 512); lds64r(vm[1] + 2, sb + vm_a + 768);
      } else {
        bar_arrive<9, 384>();
        if (w == 3) {
          if (lane == 0) {
            asm volatile("cp.async.bulk.wait_group 0;" ::: "memory");
            if (s > 0 && s < NSEG - 1 - EARLY_FLAG) FLAG_O(g_fo + (2 * (s - 1) + j) * FS);
            int it = 0;
            if (late) {
              while ((int)(ld_acquire(g_fq + (s + 1) * NH + h) - tag * 4) < 0) if (give_up(++it, 5)) break;
              asm volatile("fence.proxy.async.global;" ::: "memory");
              issue_stage(s + 1, st == 2 ? 0 : st + 1);
            }
            late = s + 2 < NSEG && (int)(fq - tag * 4) < 0;
            if (s + 2 < NSEG && !late) {
              asm volatile("fence.proxy.async.global;" ::: "memory");
              issue_stage(s + 2, st ? st - 1 : 2);
            }
          }
        } else {
          if (lane == 0 && s < NSEG - 1) { mbar_expect_tx(sb + MB_S, TX_S); mbar_expect_tx(sb + MB_V, TX_V); }
          if (s > 0) {
            const uint8_t* dp = g_qkv + (size_t)((s - 1) * NH + h) * BLK_BYTES + j * 12288 + l16 * 8;
#pragma unroll
            for (int i = 0; i < 3; i++) asm volatile("discard.global.L2 [%0], 128;" :: "l"(dp + i * 4096) : "memory");
          }
          if (lane < 10) asm volatile("st.global.v4.u32 [%0], {%1,%1,%1,%1};" :: "l"(ring + ((s - 2) & 7) * RING_SLOT + (cta >> 1) * 1024 + j * 256 + lane * 16), "r"(0) : "memory");
        }
        __syncwarp();
      }
      bar_sync<8, 128>();
      {
        uint32_t p[2][4], p4[2];
        lds128r(p[0], kv + l16); lds128r(p[1], kv + 512 + l16); lds64r(p4, kv + 1024 + (l16 >> 1));
        float o[4][4];
#pragma unroll
        for (int i = 0; i < 4; i++) mma16z(o[i], va[(i & 1) * 2][0], va[(i & 1) * 2][1], va[(i & 1) * 2][2], va[(i & 1) * 2][3], p[i >> 1][0], p[i >> 1][1]);
#pragma unroll
        for (int i = 0; i < 4; i++) mma16(o[i], va[(i & 1) * 2 + 1][0], va[(i & 1) * 2 + 1][1], va[(i & 1) * 2 + 1][2], va[(i & 1) * 2 + 1][3], p[i >> 1][2], p[i >> 1][3]);
#pragma unroll
        for (int i = 0; i < 4; i++) mma16(o[i], vm[i & 1][0], vm[i & 1][1], vm[i & 1][2], vm[i & 1][3], p4[i >> 1], p4[i >> 1]);
#pragma unroll
        for (int i = 0; i < 2; i++)
          stm4t(qx + w * 1024 + i * 512 + l16, pack_bf16(o[2 * i][0], o[2 * i][1]), pack_bf16(o[2 * i][2], o[2 * i][3]),
                pack_bf16(o[2 * i + 1][0], o[2 * i + 1][1]), pack_bf16(o[2 * i + 1][2], o[2 * i + 1][3]));
        asm volatile("fence.proxy.async.shared::cta;" ::: "memory");
      }
      if (w == 3) {
        bar_sync<5, 128>();
        if (lane == 0) {
          if (s < NSEG - 2) {
            asm volatile("cp.async.bulk.global.shared::cta.bulk_group [%0], [%1], 4096;" :: "l"(g_a + (size_t)(2 * s + j) * A_TILE + h * 4096), "r"(qx) : "memory");
            asm volatile("cp.async.bulk.commit_group;" ::: "memory");
            if (EARLY_FLAG && s == NSEG - 3) {
              asm volatile("cp.async.bulk.wait_group 0;" ::: "memory");
              FLAG_O(g_fo + (2 * s + j) * FS);
            }
          } else {
            asm volatile("cp.async.bulk.shared::cluster.shared::cta.mbarrier::complete_tx::bytes [%0], [%1], 4096, [%2];"
                         :: "r"(peer + C_KVQ + KVQ_ST + 4096 + (s & 1) * 4096), "r"(qx), "r"(peer + MB_WQ + 8 * (s & 1)) : "memory");
            mbar_expect_tx(sb + MB_WQ + 8 * (s & 1), 4096);
          }
        }
        __syncwarp();
      } else {
        bar_arrive<5, 128>();
      }
      if (++st == 3) { st = 0; stp ^= 1; }
    }
    bar_arrive<13, 384>();
    asm volatile("barrier.cluster.arrive.relaxed.aligned;" ::: "memory");
    if (w == 0 && lane == 0) atomicAdd(&g_done, 1u);
  }
}

typedef CUresult (*EncodeFn)(CUtensorMap*, CUtensorMapDataType, cuuint32_t, void*, const cuuint64_t*, const cuuint64_t*, const cuuint32_t*,
                             const cuuint32_t*, CUtensorMapInterleave, CUtensorMapSwizzle, CUtensorMapL2promotion, CUtensorMapFloatOOBfill);
static void make_map(EncodeFn enc, CUtensorMap* tm, const void* base, uint64_t cols, uint64_t rows, uint32_t bc, uint32_t br) {
  cuuint64_t dims[2] = {cols, rows};
  cuuint64_t strides[1] = {cols * 2};
  cuuint32_t box[2] = {bc, br}, es[2] = {1, 1};
  enc(tm, CU_TENSOR_MAP_DATA_TYPE_BFLOAT16, 2, const_cast<void*>(base), dims, strides, box, es, CU_TENSOR_MAP_INTERLEAVE_NONE,
      CU_TENSOR_MAP_SWIZZLE_128B, CU_TENSOR_MAP_L2_PROMOTION_L2_256B, CU_TENSOR_MAP_FLOAT_OOB_FILL_NONE);
}

static int make_map5(EncodeFn enc, CUtensorMap* tm, const void* base, uint64_t cols, uint64_t rows, uint32_t groups, bool regroup) {
  const uint64_t rb = cols * 2;
  cuuint64_t dims[5] = {cols, 2, 4, 4, rows / 32};
  cuuint64_t strides[4] = {rb, (regroup ? 8 : 2) * rb, (regroup ? 2 : 8) * rb, 32 * rb};
  cuuint32_t box[5] = {64, 2, 4, 4, groups}, es[5] = {1, 1, 1, 1, 1};
  return (int)enc(tm, CU_TENSOR_MAP_DATA_TYPE_BFLOAT16, 5, const_cast<void*>(base), dims, strides, box, es, CU_TENSOR_MAP_INTERLEAVE_NONE,
                  CU_TENSOR_MAP_SWIZZLE_128B, CU_TENSOR_MAP_L2_PROMOTION_L2_256B, CU_TENSOR_MAP_FLOAT_OOB_FILL_NONE);
}

static void build_schedule(Args& a) {
  static uint32_t lists[NGC][48];
  int cnt[NGC] = {}, nglu[NGC];
  auto fin = [](int p, int n, int k0, int nk, uint32_t mode, int keep, int parts) {
    return (uint32_t)(1 | p << 1 | n << 4 | k0 << 8 | nk << 15) | mode << 22 | (uint32_t)keep << 24 | (uint32_t)parts << 25;
  };
  const int order[8] = {3, 0, 1, 2, 4, 5, 6, 7};
  for (int c = 0; c < NGC; c++) nglu[c] = c < 8 || c >= 32 ? 0 : c < 14 ? 2 : c < 26 ? 4 : 5;
  int g = 0;
  auto add = [&](int c, uint32_t job) { lists[c][cnt[c]++] = job; };
  auto glu = [&](int c) { add(c, (uint32_t)(order[g / 14] << 1 | (g % 14) << 4 | 8 << 15)); g++; };
  for (int i = 0; i < GLU_EARLY; i++) { glu(32); glu(33); }
  for (int r = 0; r < 8; r++) for (int c = 0; c < NGC; c++) if (r < nglu[c] && g < 112) glu(c);
  const int down[8] = {8, 10, 12, 32, 14, 16, 18, 26};
  for (int q = 0; q < 16; q++) add(down[q >> 1] + (q & 1), fin(q >> 1, q & 1, 64, 28, M_STORE, 0, 0));
  for (int c = 0; c < 8; c++) add(c, fin(c >> 1, c & 1, 0, 64, M_RED, 0, 1));
  for (int q = 0; q < 4; q++) add(20 + q, fin(4, q & 1, (q >> 1) * 32, 32, M_RED, 0, 2));
  for (int q = 0; q < 8; q++) add(q < 6 ? 8 + q : 26 + q, fin(5, q & 1, (q >> 1) * 16, 16, M_RED, 0, 4));
  for (int q = 0; q < 2 * P6; q++) add(q < 8 ? q : q < 10 ? 16 + q : q < 14 ? 18 + q : q, fin(6, q & 1, (q >> 1) * (64 / P6), 64 / P6, M_RED, 0, P6));
  for (int c = 0, q = 0; c < NGC; c++) if (c != 26 && c != 27) { add(c, fin(7, q & 1, (q >> 1) * 4, 4, M_RED, 0, 16)); q++; }
  int o = 0;
  for (int c = 0; c < NGC; c++) { a.first[c] = (uint16_t)o; for (int i = 0; i < cnt[c]; i++) a.job[o++] = lists[c][i]; }
  a.first[NGC] = (uint16_t)o; a.first[NGC + 1] = 0; a.zero = 0;
  for (; o < MAXJOBS; o++) a.job[o] = 0;
}

extern "C" void kernel_launch(void* const* d_in, const int* in_sizes, int n_in, void* d_out, int out_size) {
  (void)in_sizes; (void)n_in; (void)out_size;
  const bf16 *wq = (const bf16*)d_in[2], *wk = (const bf16*)d_in[3], *wv = (const bf16*)d_in[4], *wo = (const bf16*)d_in[5],
             *wg = (const bf16*)d_in[8], *wu = (const bf16*)d_in[9], *wd = (const bf16*)d_in[10];
  static EncodeFn enc = nullptr;
  static Args a;
  if (!enc) {
    void* fn = nullptr; cudaDriverEntryPointQueryResult qr;
    cudaGetDriverEntryPoint("cuTensorMapEncodeTiled", &fn, cudaEnableDefault, &qr);
    enc = (EncodeFn)fn;
    cudaFuncSetAttribute(fused_kernel, cudaFuncAttributeMaxDynamicSharedMemorySize, K_SMEM);
    build_schedule(a);
  }
  make_map(enc, &a.tmq, wq, HD, DM, 64, 128); make_map(enc, &a.tmk, wk, HD, DM, 64, 128); make_map(enc, &a.tmv, wv, HD, DM, 64, 128);
  make_map(enc, &a.tmo, wo, DM, HD, 64, 128);
  int rc = make_map5(enc, &a.pw[0], wk, HD, DM, 4, true) | make_map5(enc, &a.pw[1], wv, HD, DM, 4, true) | make_map5(enc, &a.pw[2], wq, HD, DM, 4, true) |
           make_map5(enc, &a.pb[0], wg, FF, DM, 2, true) | make_map5(enc, &a.pb[1], wu, FF, DM, 2, true) |
           make_map5(enc, &a.pb[2], wo, DM, HD, 2, true) | make_map5(enc, &a.pb[3], wd, DM, FF, 2, false);
  if (rc) return;
  a.x = (const bf16*)d_in[0]; a.mem0 = (const bf16*)d_in[1]; a.wo = wo; a.gate_w = (const bf16*)d_in[11]; a.out = (bf16*)d_out;
  cudaLaunchConfig_t cfg = {};
  cfg.gridDim = dim3(NCTA); cfg.blockDim = dim3(384); cfg.dynamicSmemBytes = K_SMEM; cfg.stream = cudaStreamPerThread;
  cudaLaunchAttribute at[1];
  at[0].id = cudaLaunchAttributeClusterDimension; at[0].val.clusterDim.x = 2; at[0].val.clusterDim.y = 1; at[0].val.clusterDim.z = 1;
  cfg.attrs = at; cfg.numAttrs = 1;
  cudaLaunchKernelEx(&cfg, fused_kernel, a);
}
```
